```python
import torch

def _softmax(x, axis=-1):
    return torch.softmax(x, dim=axis)
def _gelu(x):
    return torch.nn.functional.gelu(x, approximate="tanh")
def _silu(x):
    return torch.nn.functional.silu(x)
def _sigmoid(x):
    return torch.sigmoid(x)
def _layernorm(x, axis=-1, eps=1e-5):
    m = x.mean(dim=axis, keepdim=True)
    v = x.var(dim=axis, keepdim=True, unbiased=False)
    return (x - m) / torch.sqrt(v + eps)
def _scatter_add(tgt, idx, src, axis=0):
    return tgt.clone().index_add_(axis, idx, src)
def _segment_sum(src, seg, n):
    out = torch.zeros((n,) + src.shape[1:], dtype=src.dtype)
    return out.index_add_(0, seg, src)
def _pad(x, pw):
    flat = tuple(v for pair in reversed(pw) for v in pair)
    return torch.nn.functional.pad(x, flat)

kernel_name = 'sequential_preLN__softmax_full_mha__dense_activation_squared_relu__prompt'

def setup_inputs():

    _w = (lambda a: (lambda t: t.to(torch.bfloat16) if t.is_floating_point() else t)(torch.as_tensor(a)))
    def _A_setup():
        B, S, D = 1, 2048, 640
        return {
            "x": _w((lambda *s: torch.randn(*s, dtype=torch.bfloat16) * 0.05)(B, S, D)),
            "wqkv": _w((lambda *s: torch.randn(*s, dtype=torch.bfloat16) * 0.05)(D, 3 * D)),
            "wo": _w((lambda *s: torch.randn(*s, dtype=torch.bfloat16) * 0.05)(D, D)),
        }
    _A_in = _A_setup()

    def _B_setup():
        B, S, D, F = 1, 2048, 640, 1536
        return {
            "x": _w((lambda *s: torch.randn(*s, dtype=torch.bfloat16) * 0.05)(B, S, D)),
            "w1": _w((lambda *s: torch.randn(*s, dtype=torch.bfloat16) * 0.05)(D, F)),
            "b1": _w((lambda *s: torch.randn(*s, dtype=torch.bfloat16) * 0.8)(F)),
            "w2": _w((lambda *s: torch.randn(*s, dtype=torch.bfloat16) * 0.05)(F, D)),
            "b2": _w((lambda *s: torch.randn(*s, dtype=torch.bfloat16) * 3.2)(D)),
        }
    _B_in = _B_setup()

    return {
        "A_x": _A_in["x"],
        "A_wqkv": _A_in["wqkv"],
        "A_wo": _A_in["wo"],
        "B_x": _B_in["x"],
        "B_w1": _B_in["w1"],
        "B_b1": _B_in["b1"],
        "B_w2": _B_in["w2"],
        "B_b2": _B_in["b2"],
    }

def reference(A_x, A_wqkv, A_wo, B_x, B_w1, B_b1, B_w2, B_b2):
    def _A_ref(x, wqkv, wo):
        B, S, D = x.shape
        H = 32; Dh = D // H
        qkv = (lambda x, *d: x.permute(*d))((x @ wqkv).reshape(B, S, 3, H, Dh), 2, 0, 3, 1, 4)
        q, k, v = qkv[0], qkv[1], qkv[2]
        scale = Dh ** -0.5
        scores = torch.einsum("bhqd,bhkd->bhqk", q, k) * scale
        p = _softmax(scores, axis=-1)
        o = torch.einsum("bhqk,bhkd->bhqd", p, v)
        return (lambda x, *d: x.permute(*d))(o, 0, 2, 1, 3).reshape(B, S, D) @ wo

    def _B_ref(x, w1, b1, w2, b2):
        h = torch.einsum("bsd,df->bsf", x, w1) + b1
        zero = torch.zeros_like(h)
        r = torch.where(h > zero, h, zero)
        h = r * r
        out = torch.einsum("bsf,fd->bsd", h, w2) + b2
        return out

    x = A_x
    h = x + _A_ref(_layernorm(x, axis=-1), A_wqkv, A_wo)
    h2 = h + _B_ref(_layernorm(h, axis=-1), B_w1, B_b1, B_w2, B_b2)
    return h2
```

```cpp
#include <cuda_runtime.h>
#include <cuda_bf16.h>
#include <cuda.h>
#include <stdint.h>

namespace {

template <uint32_t HB>
__device__ __forceinline__ void wgmma_rs_n24_tb1_a(float (&d)[12], uint32_t a0, uint32_t a1, uint32_t a2, uint32_t a3, uint32_t db) {
  asm volatile("{\n.reg .b64 db;\nmov.b64 db, {%16, %17};\n"
    "wgmma.mma_async.sync.aligned.m64n24k16.f32.bf16.bf16 "
    "{%0, %1, %2, %3, %4, %5, %6, %7, %8, %9, %10, %11}, "
    "{%12,%13,%14,%15}, db, 1, 1, 1, 1;\n}\n"
    : "+f"(d[0]), "+f"(d[1]), "+f"(d[2]), "+f"(d[3]), "+f"(d[4]), "+f"(d[5]), "+f"(d[6]), "+f"(d[7]), "+f"(d[8]), "+f"(d[9]),
      "+f"(d[10]), "+f"(d[11])
    : "r"(a0), "r"(a1), "r"(a2), "r"(a3), "r"(db), "n"(HB));
}
template <uint32_t HB>
__device__ __forceinline__ void wgmma_rs_n64_tb0_a(float (&d)[32], uint32_t a0, uint32_t a1, uint32_t a2, uint32_t a3, uint32_t db) {
  asm volatile("{\n.reg .b64 db;\nmov.b64 db, {%36, %37};\n"
    "wgmma.mma_async.sync.aligned.m64n64k16.f32.bf16.bf16 "
    "{%0, %1, %2, %3, %4, %5, %6, %7, %8, %9, %10, %11, %12, %13, %14, %15, %16, %17, %18, %19, "
    "%20, %21, %22, %23, %24, %25, %26, %27, %28, %29, %30, %31}, "
    "{%32,%33,%34,%35}, db, 1, 1, 1, 0;\n}\n"
    : "+f"(d[0]), "+f"(d[1]), "+f"(d[2]), "+f"(d[3]), "+f"(d[4]), "+f"(d[5]), "+f"(d[6]), "+f"(d[7]), "+f"(d[8]), "+f"(d[9]),
      "+f"(d[10]), "+f"(d[11]), "+f"(d[12]), "+f"(d[13]), "+f"(d[14]), "+f"(d[15]), "+f"(d[16]), "+f"(d[17]), "+f"(d[18]), "+f"(d[19]),
      "+f"(d[20]), "+f"(d[21]), "+f"(d[22]), "+f"(d[23]), "+f"(d[24]), "+f"(d[25]), "+f"(d[26]), "+f"(d[27]), "+f"(d[28]), "+f"(d[29]),
      "+f"(d[30]), "+f"(d[31])
    : "r"(a0), "r"(a1), "r"(a2), "r"(a3), "r"(db), "n"(HB));
}
template <uint32_t HB>
__device__ __forceinline__ void wgmma_rs_n64_tb0_z(float (&d)[32], uint32_t a0, uint32_t a1, uint32_t a2, uint32_t a3, uint32_t db) {
  asm volatile("{\n.reg .b64 db;\nmov.b64 db, {%36, %37};\n"
    "wgmma.mma_async.sync.aligned.m64n64k16.f32.bf16.bf16 "
    "{%0, %1, %2, %3, %4, %5, %6, %7, %8, %9, %10, %11, %12, %13, %14, %15, %16, %17, %18, %19, "
    "%20, %21, %22, %23, %24, %25, %26, %27, %28, %29, %30, %31}, "
    "{%32,%33,%34,%35}, db, 0, 1, 1, 0;\n}\n"
    : "=f"(d[0]), "=f"(d[1]), "=f"(d[2]), "=f"(d[3]), "=f"(d[4]), "=f"(d[5]), "=f"(d[6]), "=f"(d[7]), "=f"(d[8]), "=f"(d[9]),
      "=f"(d[10]), "=f"(d[11]), "=f"(d[12]), "=f"(d[13]), "=f"(d[14]), "=f"(d[15]), "=f"(d[16]), "=f"(d[17]), "=f"(d[18]), "=f"(d[19]),
      "=f"(d[20]), "=f"(d[21]), "=f"(d[22]), "=f"(d[23]), "=f"(d[24]), "=f"(d[25]), "=f"(d[26]), "=f"(d[27]), "=f"(d[28]), "=f"(d[29]),
      "=f"(d[30]), "=f"(d[31])
    : "r"(a0), "r"(a1), "r"(a2), "r"(a3), "r"(db), "n"(HB));
}
template <uint32_t HA, uint32_t HB>
__device__ __forceinline__ void wgmma_ss_n120_tb1_a(float (&d)[60], uint32_t da, uint32_t db) {
  asm volatile("{\n.reg .b64 da, db;\nmov.b64 da, {%60, %62};\nmov.b64 db, {%61, %63};\n"
    "wgmma.mma_async.sync.aligned.m64n120k16.f32.bf16.bf16 "
    "{%0, %1, %2, %3, %4, %5, %6, %7, %8, %9, %10, %11, %12, %13, %14, %15, %16, %17, %18, %19, "
    "%20, %21, %22, %23, %24, %25, %26, %27, %28, %29, %30, %31, %32, %33, %34, %35, %36, %37, %38, %39, "
    "%40, %41, %42, %43, %44, %45, %46, %47, %48, %49, %50, %51, %52, %53, %54, %55, %56, %57, %58, %59}, "
    "da, db, 1, 1, 1, 0, 1;\n}\n"
    : "+f"(d[0]), "+f"(d[1]), "+f"(d[2]), "+f"(d[3]), "+f"(d[4]), "+f"(d[5]), "+f"(d[6]), "+f"(d[7]), "+f"(d[8]), "+f"(d[9]),
      "+f"(d[10]), "+f"(d[11]), "+f"(d[12]), "+f"(d[13]), "+f"(d[14]), "+f"(d[15]), "+f"(d[16]), "+f"(d[17]), "+f"(d[18]), "+f"(d[19]),
      "+f"(d[20]), "+f"(d[21]), "+f"(d[22]), "+f"(d[23]), "+f"(d[24]), "+f"(d[25]), "+f"(d[26]), "+f"(d[27]), "+f"(d[28]), "+f"(d[29]),
      "+f"(d[30]), "+f"(d[31]), "+f"(d[32]), "+f"(d[33]), "+f"(d[34]), "+f"(d[35]), "+f"(d[36]), "+f"(d[37]), "+f"(d[38]), "+f"(d[39]),
      "+f"(d[40]), "+f"(d[41]), "+f"(d[42]), "+f"(d[43]), "+f"(d[44]), "+f"(d[45]), "+f"(d[46]), "+f"(d[47]), "+f"(d[48]), "+f"(d[49]),
      "+f"(d[50]), "+f"(d[51]), "+f"(d[52]), "+f"(d[53]), "+f"(d[54]), "+f"(d[55]), "+f"(d[56]), "+f"(d[57]), "+f"(d[58]), "+f"(d[59])
    : "r"(da), "r"(db), "n"(HA), "n"(HB));
}
template <uint32_t HA, uint32_t HB>
__device__ __forceinline__ void wgmma_ss_n80_tb1_a(float (&d)[40], uint32_t da, uint32_t db) {
  asm volatile("{\n.reg .b64 da, db;\nmov.b64 da, {%40, %42};\nmov.b64 db, {%41, %43};\n"
    "wgmma.mma_async.sync.aligned.m64n80k16.f32.bf16.bf16 "
    "{%0, %1, %2, %3, %4, %5, %6, %7, %8, %9, %10, %11, %12, %13, %14, %15, %16, %17, %18, %19, "
    "%20, %21, %22, %23, %24, %25, %26, %27, %28, %29, %30, %31, %32, %33, %34, %35, %36, %37, %38, %39}, "
    "da, db, 1, 1, 1, 0, 1;\n}\n"
    : "+f"(d[0]), "+f"(d[1]), "+f"(d[2]), "+f"(d[3]), "+f"(d[4]), "+f"(d[5]), "+f"(d[6]), "+f"(d[7]), "+f"(d[8]), "+f"(d[9]),
      "+f"(d[10]), "+f"(d[11]), "+f"(d[12]), "+f"(d[13]), "+f"(d[14]), "+f"(d[15]), "+f"(d[16]), "+f"(d[17]), "+f"(d[18]), "+f"(d[19]),
      "+f"(d[20]), "+f"(d[21]), "+f"(d[22]), "+f"(d[23]), "+f"(d[24]), "+f"(d[25]), "+f"(d[26]), "+f"(d[27]), "+f"(d[28]), "+f"(d[29]),
      "+f"(d[30]), "+f"(d[31]), "+f"(d[32]), "+f"(d[33]), "+f"(d[34]), "+f"(d[35]), "+f"(d[36]), "+f"(d[37]), "+f"(d[38]), "+f"(d[39])
    : "r"(da), "r"(db), "n"(HA), "n"(HB));
}
template <uint32_t HA, uint32_t HB>
__device__ __forceinline__ void wgmma_ss_n96_tb1_a(float (&d)[48], uint32_t da, uint32_t db) {
  asm volatile("{\n.reg .b64 da, db;\nmov.b64 da, {%48, %50};\nmov.b64 db, {%49, %51};\n"
    "wgmma.mma_async.sync.aligned.m64n96k16.f32.bf16.bf16 "
    "{%0, %1, %2, %3, %4, %5, %6, %7, %8, %9, %10, %11, %12, %13, %14, %15, %16, %17, %18, %19, "
    "%20, %21, %22, %23, %24, %25, %26, %27, %28, %29, %30, %31, %32, %33, %34, %35, %36, %37, %38, %39, "
    "%40, %41, %42, %43, %44, %45, %46, %47}, "
    "da, db, 1, 1, 1, 0, 1;\n}\n"
    : "+f"(d[0]), "+f"(d[1]), "+f"(d[2]), "+f"(d[3]), "+f"(d[4]), "+f"(d[5]), "+f"(d[6]), "+f"(d[7]), "+f"(d[8]), "+f"(d[9]),
      "+f"(d[10]), "+f"(d[11]), "+f"(d[12]), "+f"(d[13]), "+f"(d[14]), "+f"(d[15]), "+f"(d[16]), "+f"(d[17]), "+f"(d[18]), "+f"(d[19]),
      "+f"(d[20]), "+f"(d[21]), "+f"(d[22]), "+f"(d[23]), "+f"(d[24]), "+f"(d[25]), "+f"(d[26]), "+f"(d[27]), "+f"(d[28]), "+f"(d[29]),
      "+f"(d[30]), "+f"(d[31]), "+f"(d[32]), "+f"(d[33]), "+f"(d[34]), "+f"(d[35]), "+f"(d[36]), "+f"(d[37]), "+f"(d[38]), "+f"(d[39]),
      "+f"(d[40]), "+f"(d[41]), "+f"(d[42]), "+f"(d[43]), "+f"(d[44]), "+f"(d[45]), "+f"(d[46]), "+f"(d[47])
    : "r"(da), "r"(db), "n"(HA), "n"(HB));
}

constexpr int HEADB = 98304;
constexpr uint32_t POLY = 0xDA;
constexpr int KB = 1024;
#define XW 0
#define XA 0
#define XB 0
constexpr int SMEM_BYTES = 227 * KB;

__device__ __align__(1024) uint8_t g_img[96 * HEADB];
__device__ __align__(1024) uint8_t g_O[32 * 81920];
__device__ __align__(1024) uint8_t g_H[32 * 81920];
__device__ __align__(1024) uint8_t g_G[32 * 196608];
__device__ __align__(1024) uint8_t g_Wo[8 * 102400];
__device__ __align__(1024) uint8_t g_W1[8 * 245760];
__device__ __align__(1024) uint8_t g_W2[8 * 245760];
__device__ __align__(128) float g_cs1[8 * 1536];
__device__ __align__(128) float2 g_st1[2048];
__device__ __align__(128) float g_csq[8 * 16 * 240];
__device__ __align__(128) float g_nrm[96 * 64];
__device__ __align__(128) float2 g_st2[16 * 8 * 128];
constexpr int C_EPOCH = 0, C_A = 32, C_W = 64, C_Q0 = 128, C_QA = C_Q0 + 96 * 8, C_O = C_QA + 96 * 8, C_H = C_O + 32 * 32, C_G = C_H + 32 * 32,
              C_END = C_G + 32 * 32;
__device__ __align__(128) uint32_t g_cnt[C_END];
#define TS(i) do {} while (0)
#define TSG(i) do {} while (0)

constexpr int SM_RED = 192 * KB;
constexpr int SM_STG = 120 * KB;
constexpr int SM_Q = 192 * KB;
constexpr int SM_HOWN = 196 * KB;
__device__ __forceinline__ int a3_slot(int m, int kc) { return m ? 132 * KB + (kc & 7) * 8 * KB : 100 * KB + kc * 8 * KB; }
__device__ __forceinline__ int b4_slot(int i) { const int s = i & 3; return s == 0 ? 102 * KB : s == 1 ? 0 : 2 * KB + (s - 1) * 30 * KB; }
__device__ __forceinline__ int a4_slot(int m, int i) { return (m ? 132 * KB : 164 * KB) + ((i - 1) % 3) * 10 * KB; }
__device__ __forceinline__ int b5_slot(int i) { return 32 * KB + ((i + 6) % 10) * 10 * KB; }
__device__ __forceinline__ int a5_slot(int m, int i) { const int s = i % 6; return s < 4 ? (m ? 132 * KB : 164 * KB) + s * 8 * KB : m * 16 * KB + (s - 4) * 8 * KB; }
constexpr int SM_MISC = 216 * KB;
constexpr int SM_BAR = SM_MISC;
constexpr int SM_CSQ = SM_MISC + 2048;
constexpr int SM_ST1 = SM_CSQ + 1024;
constexpr int SM_CS1 = SM_ST1 + 1024;
constexpr int SM_B1 = SM_CS1 + 768;
constexpr int SM_B2 = SM_B1 + 768;
constexpr int SM_UNS = SM_B2 + 384;
constexpr int B_F1 = 0, B_RAW1 = 10, B_AUX1 = 11, B_SDONE = 12, B_KV = 13, B_UNS = 21, B_WO = 22, B_F3 = 23, B_F4B = 43, B_F4A = 51,
              B_F5B = 67, B_F5A = 91, B_C4 = 139,
              B_D3 = 139, B_HOWN = 159, B_D5 = 161, B_C8 = 209,
              B_STG1 = 209, B_D4 = 211, B_GOWN = 227, B_C16 = 229,
              B_D1 = 229, B_NRM1 = 239, B_KVF = 240, B_END = 244;

__device__ __forceinline__ void wfence() { asm volatile("wgmma.fence.sync.aligned;" ::: "memory"); }
__device__ __forceinline__ void wcommit() { asm volatile("wgmma.commit_group.sync.aligned;" ::: "memory"); }
template <int N> __device__ __forceinline__ void wwait() { asm volatile("wgmma.wait_group.sync.aligned %0;" ::"n"(N) : "memory"); }
__device__ __forceinline__ uint32_t dlo(uint32_t addr, uint32_t lbo) { return ((addr & 0x3FFFF) >> 4) | ((lbo >> 4) << 16); }
constexpr uint32_t dhi(uint32_t sbo, uint32_t swz) { return (sbo >> 4) | (swz << 30); }
constexpr uint32_t H128 = dhi(128, 0), H384 = dhi(384, 0), HSW = dhi(1024, 1);
__device__ __forceinline__ void mbar_init(uint32_t b, int c) { asm volatile("mbarrier.init.shared::cta.b64 [%0], %1;" ::"r"(b), "r"(c) : "memory"); }
__device__ __forceinline__ void mbar_expect(uint32_t b, int bytes) { asm volatile("mbarrier.arrive.expect_tx.shared::cta.b64 _, [%0], %1;" ::"r"(b), "r"(bytes) : "memory"); }
__device__ __forceinline__ void mbar_arrive(uint32_t b) { asm volatile("mbarrier.arrive.shared::cta.b64 _, [%0];" ::"r"(b) : "memory"); }
__device__ __forceinline__ void mbar_wait(uint32_t b) {
  asm volatile("{\n.reg .pred p;\n.reg .u32 c;\nmov.u32 c,0;\nL1:\nmbarrier.try_wait.parity.shared::cta.b64 p, [%0], 0;\n@p bra L2;\n"
               "add.u32 c,c,1;\nsetp.lt.u32 p,c,4000000;\n@p bra L1;\ntrap;\nL2:\n}" ::"r"(b) : "memory");
}
__device__ __forceinline__ void bulk_g2s(uint32_t dst, const void* src, int bytes, uint32_t bar) {
  asm volatile("cp.async.bulk.shared::cluster.global.mbarrier::complete_tx::bytes [%0], [%1], %2, [%3];" ::"r"(dst), "l"(src), "r"(bytes), "r"(bar) : "memory");
}
__device__ __forceinline__ void bulk_s2g(void* dst, uint32_t src, int bytes) {
  asm volatile("cp.async.bulk.global.shared::cta.bulk_group [%0], [%1], %2;" ::"l"(dst), "r"(src), "r"(bytes) : "memory");
}
__device__ __forceinline__ void bulk_commit() { asm volatile("cp.async.bulk.commit_group;" ::: "memory"); }
__device__ __forceinline__ void bulk_wait0() { asm volatile("cp.async.bulk.wait_group 0;" ::: "memory"); }
__device__ __forceinline__ void tma2d(uint32_t dst, const CUtensorMap* tm, int c0, int c1, uint32_t bar) {
  asm volatile("cp.async.bulk.tensor.2d.shared::cluster.global.mbarrier::complete_tx::bytes [%0], [%1, {%3, %4}], [%2];" ::"r"(dst), "l"(tm), "r"(bar), "r"(c0), "r"(c1) : "memory");
}
__device__ __forceinline__ void fence_async_smem() { asm volatile("fence.proxy.async.shared::cta;" ::: "memory"); }
__device__ __forceinline__ void fence_async_all() { asm volatile("fence.proxy.async.global;" ::: "memory"); }
__device__ __forceinline__ void bar_arrive(int id, int n) { asm volatile("bar.arrive %0, %1;" ::"r"(id), "r"(n) : "memory"); }
__device__ __forceinline__ void bar_sync(int id, int n) { asm volatile("bar.sync %0, %1;" ::"r"(id), "r"(n) : "memory"); }
__device__ __forceinline__ void red_release(uint32_t* p) { asm volatile("red.release.gpu.global.add.u32 [%0], 1;" ::"l"(p) : "memory"); }
__device__ __forceinline__ uint32_t ld_acquire(const uint32_t* p) { uint32_t v; asm volatile("ld.acquire.gpu.global.u32 %0, [%1];" : "=r"(v) : "l"(p) : "memory"); return v; }
__device__ __forceinline__ void poll_all(const uint32_t* p, uint32_t target, bool act) {
  for (int it = 0;; it++) {
    bool ok = true;
    if (act) ok = (int32_t)(ld_acquire(p) - target) >= 0;
    if (__all_sync(~0u, ok)) break;
    if (it > 2000000) __trap();
  }
}
__device__ __forceinline__ uint32_t poll_mask(const uint32_t* p8, uint32_t target, int lane, uint32_t mask, int need) {
  for (int it = 0; !((mask >> need) & 1); it++) {
    bool ok = false;
    if (lane < 8) ok = (int32_t)(ld_acquire(p8 + lane) - target) >= 0;
    mask = __ballot_sync(~0u, ok);
    if (it > 2000000) __trap();
  }
  return mask;
}
__device__ __forceinline__ float ex2(float x) { float y; asm("ex2.approx.ftz.f32 %0, %1;" : "=f"(y) : "f"(x)); return y; }
__device__ __forceinline__ float rcp(float x) { float y; asm("rcp.approx.ftz.f32 %0, %1;" : "=f"(y) : "f"(x)); return y; }
__device__ __forceinline__ uint32_t packbf(float lo, float hi) { uint32_t r; asm("cvt.rn.bf16x2.f32 %0, %1, %2;" : "=r"(r) : "f"(hi), "f"(lo)); return r; }
__device__ __forceinline__ float bflo(uint32_t v) { return __uint_as_float(v << 16); }
__device__ __forceinline__ float bfhi(uint32_t v) { return __uint_as_float(v & 0xFFFF0000u); }
__device__ __forceinline__ void sts32(uint32_t a, uint32_t v) { asm volatile("st.shared.b32 [%0], %1;" ::"r"(a), "r"(v) : "memory"); }
__device__ __forceinline__ void sts64(uint32_t a, uint32_t v0, uint32_t v1) { asm volatile("st.shared.v2.b32 [%0], {%1,%2};" ::"r"(a), "r"(v0), "r"(v1) : "memory"); }
__device__ __forceinline__ void sts128f(uint32_t a, float4 v) { asm volatile("st.shared.v4.f32 [%0], {%1,%2,%3,%4};" ::"r"(a), "f"(v.x), "f"(v.y), "f"(v.z), "f"(v.w) : "memory"); }
__device__ __forceinline__ uint32_t lds32(uint32_t a) { uint32_t v; asm volatile("ld.shared.b32 %0, [%1];" : "=r"(v) : "r"(a) : "memory"); return v; }
__device__ __forceinline__ float2 lds64f(uint32_t a) { float2 v; asm volatile("ld.shared.v2.f32 {%0,%1}, [%2];" : "=f"(v.x), "=f"(v.y) : "r"(a) : "memory"); return v; }
__device__ __forceinline__ uint2 lds64(uint32_t a) { uint2 v; asm volatile("ld.shared.v2.b32 {%0,%1}, [%2];" : "=r"(v.x), "=r"(v.y) : "r"(a) : "memory"); return v; }
__device__ __forceinline__ uint4 lds128(uint32_t a) { uint4 v; asm volatile("ld.shared.v4.b32 {%0,%1,%2,%3}, [%4];" : "=r"(v.x), "=r"(v.y), "=r"(v.z), "=r"(v.w) : "r"(a) : "memory"); return v; }
__device__ __forceinline__ float4 lds128f(uint32_t a) { float4 v; asm volatile("ld.shared.v4.f32 {%0,%1,%2,%3}, [%4];" : "=f"(v.x), "=f"(v.y), "=f"(v.z), "=f"(v.w) : "r"(a) : "memory"); return v; }
__device__ __forceinline__ void stsm4(uint32_t a, uint32_t r0, uint32_t r1, uint32_t r2, uint32_t r3) {
  asm volatile("stmatrix.sync.aligned.m8n8.x4.shared.b16 [%0], {%1,%2,%3,%4};" ::"r"(a), "r"(r0), "r"(r1), "r"(r2), "r"(r3) : "memory");
}
__device__ __forceinline__ float ldcg_f(const float* p) { float v; asm volatile("ld.global.cg.f32 %0, [%1];" : "=f"(v) : "l"(p) : "memory"); return v; }
__device__ __forceinline__ float2 ldcg_f2(const float2* p) { float2 v; asm volatile("ld.global.cg.v2.f32 {%0,%1}, [%2];" : "=f"(v.x), "=f"(v.y) : "l"(p) : "memory"); return v; }
__device__ __forceinline__ float qsum(float v) { v += __shfl_xor_sync(~0u, v, 1); v += __shfl_xor_sync(~0u, v, 2); return v; }
__device__ __forceinline__ float sq2(uint32_t v, float a) { float l = bflo(v), h = bfhi(v); return fmaf(h, h, fmaf(l, l, a)); }
template <int N> __device__ __forceinline__ void zero_acc(float (&a)[N]) {
#pragma unroll
  for (int i = 0; i < N; i++) { a[i] = 0.f; asm volatile("" : "+f"(a[i])::"memory"); }
}

__device__ __forceinline__ uint32_t exp2_pair(float t0, float t1) {
  uint32_t u, mh, e, r;
  asm("prmt.b32 %0, %1, %2, 0x6521;" : "=r"(u) : "r"(__float_as_uint(t0)), "r"(__float_as_uint(t1)));
  asm("lop3.b32 %0, %1, 0x007F007F, %2, 0xEA;" : "=r"(mh) : "r"(u), "r"(0x3F003F00u));
  asm("lop3.b32 %0, %1, 0xFF80FF80, %2, 0xEA;" : "=r"(e) : "r"(u), "r"(0x00010001u));
  asm("fma.rn.bf16x2 %0, %1, %2, %3;" : "=r"(r) : "r"(u), "r"(mh), "r"(e));
  return r;
}

struct Params {
  const __nv_bfloat16 *x, *wqkv, *wo, *w1, *b1, *w2, *b2;
  __nv_bfloat16* out;
};

__device__ __forceinline__ void helper_warp(const Params& p, int gw, uint32_t bar) {
  const int lane = threadIdx.x & 31, k8 = lane >> 2, q = lane & 3;
  mbar_wait(bar + 8 * (B_KV + 1));
  if (gw < 320) {
    const int kb = gw >> 2, kp = kb * 8 + k8, pr = kp / 40, r = kp % 40;
    const int k = pr * 40 + (r < 16 ? r : r < 32 ? r + 4 : r < 36 ? r - 16 : r);
    const int nb0 = (gw & 3) * 20 + q;
    const uint4* src = (const uint4*)(p.wo + k * 640) + nb0;
    uint4 v[5];
#pragma unroll
    for (int i = 0; i < 5; i++) v[i] = __ldg(src + i * 4);
#pragma unroll
    for (int i = 0; i < 5; i++) {
      const int nbg = nb0 + i * 4;
      *(uint4*)(g_Wo + (nbg / 10) * 102400 + kb * 1280 + (nbg % 10) * 128 + k8 * 16) = v[i];
    }
  }
  {
    const int nbg = (gw % 48) * 4 + q, kb0 = (gw / 48) * 10;
    const uint4* src = (const uint4*)(p.w1 + (kb0 * 8 + k8) * 1536) + nbg;
    uint4* dst = (uint4*)(g_W1 + (nbg / 24) * 245760 + kb0 * 3072 + (nbg % 24) * 128 + k8 * 16);
    float s[8] = {0, 0, 0, 0, 0, 0, 0, 0};
#pragma unroll 1
    for (int i0 = 0; i0 < 10; i0 += 2) {
      uint4 v[2];
#pragma unroll
      for (int i = 0; i < 2; i++) v[i] = __ldg(src + (i0 + i) * 1536);
#pragma unroll
      for (int i = 0; i < 2; i++) {
        dst[(i0 + i) * 192] = v[i];
        s[0] += bflo(v[i].x); s[1] += bfhi(v[i].x); s[2] += bflo(v[i].y); s[3] += bfhi(v[i].y);
        s[4] += bflo(v[i].z); s[5] += bfhi(v[i].z); s[6] += bflo(v[i].w); s[7] += bfhi(v[i].w);
      }
    }
#pragma unroll
    for (int i = 0; i < 8; i++) {
      s[i] += __shfl_xor_sync(~0u, s[i], 4); s[i] += __shfl_xor_sync(~0u, s[i], 8); s[i] += __shfl_xor_sync(~0u, s[i], 16);
    }
    if (k8 == 0) {
      float4* cp = (float4*)(g_cs1 + (gw / 48) * 1536 + nbg * 8);
      cp[0] = make_float4(s[0], s[1], s[2], s[3]);
      cp[1] = make_float4(s[4], s[5], s[6], s[7]);
    }
  }
#pragma unroll 1
  for (int hf = 0; hf < 2; hf++) {
    const int kb = gw >> 1, nb0 = ((gw & 1) * 2 + hf) * 20 + q;
    const uint4* src = (const uint4*)(p.w2 + (kb * 8 + k8) * 640) + nb0;
    uint4 v[5];
#pragma unroll
    for (int i = 0; i < 5; i++) v[i] = __ldg(src + i * 4);
#pragma unroll
    for (int i = 0; i < 5; i++) {
      const int nbg = nb0 + i * 4;
      *(uint4*)(g_W2 + (nbg / 10) * 245760 + kb * 1280 + (nbg % 10) * 128 + k8 * 16) = v[i];
    }
  }
  __syncwarp();
  if (lane == 0) { red_release(g_cnt + C_W); TS(28); }
  __syncwarp();
}

__device__ __forceinline__ int half_gh(int j, int nh) { return (j + 8 * nh) * 6; }
__device__ __forceinline__ int slice_of(int j, int i) { return i == 0 ? j : (i - 1 < j ? i - 1 : i); }

__device__ __forceinline__ void load_stage1(const CUtensorMap* tmx, const CUtensorMap* tmw, uint32_t sb, int kc, int rb, int j) {
  const uint32_t s = sb + (kc & 3) * 48 * KB, f = sb + SM_BAR + 8 * (B_F1 + kc);
  mbar_expect(f, 48 * KB);
  tma2d(s + 16 * KB, tmw, j * 120, kc * 64, f);
  tma2d(s + 24 * KB, tmw, j * 120 + 64, kc * 64, f);
  tma2d(s, tmx, kc * 64, rb * 128, f);
  tma2d(s + 32 * KB, tmw, j * 120 + 960, kc * 64, f);
  tma2d(s + 40 * KB, tmw, j * 120 + 1024, kc * 64, f);
}

__device__ __forceinline__ void warp_weights(const CUtensorMap* tmx, const CUtensorMap* tmw, const Params& p, uint32_t sb, int rb, int j, int head, int quarter) {
  const int lane = threadIdx.x & 31;
  const uint32_t bar = sb + SM_BAR;
  const uint32_t ep = ld_acquire(g_cnt + C_EPOCH) + 1;
  if (lane == 0) {
#pragma unroll 1
    for (int kc = 4; kc < 10; kc++) {
      mbar_wait(bar + 8 * (B_D1 + kc - 4));
      load_stage1(tmx, tmw, sb, kc, rb, j);
    }
  }
  __syncwarp();
  poll_all(g_cnt + C_A, ep * 128, lane == 0);
  if (lane == 0) {
    fence_async_all();
    mbar_expect(bar + 8 * B_RAW1, 15360 + 1024);
    bulk_g2s(sb + SM_RED, g_csq + j * 16 * 240, 15360, bar + 8 * B_RAW1);
    bulk_g2s(sb + SM_ST1, g_st1 + rb * 128, 1024, bar + 8 * B_RAW1);
  }
  mbar_wait(bar + 8 * B_RAW1);
  if (lane < 30) {
    float4 a = make_float4(0, 0, 0, 0), b = a;
#pragma unroll 4
    for (int i = 0; i < 16; i++) {
      const float4 u = lds128f(sb + SM_RED + i * 960 + lane * 32), v = lds128f(sb + SM_RED + i * 960 + lane * 32 + 16);
      a.x += u.x; a.y += u.y; a.z += u.z; a.w += u.w; b.x += v.x; b.y += v.y; b.z += v.z; b.w += v.w;
    }
    sts128f(sb + SM_CSQ + lane * 32, a); sts128f(sb + SM_CSQ + lane * 32 + 16, b);
  }
  fence_async_smem();
  __syncwarp();
  if (lane == 0) mbar_arrive(bar + 8 * B_AUX1);
  const int ty = lane >> 2, pc = lane & 3;
  const uint8_t* img = g_img + (size_t)(ty * 32 + head) * HEADB + pc * 6144;
  poll_all(g_cnt + C_Q0 + (head + 32 * lane) * 8 + (lane == 0 ? quarter : (head & 3)), ep * 4, lane < 3);
  mbar_wait(bar + 8 * (B_D1 + 9));
  if (lane == 0) { TS(17); mbar_expect(bar + 8 * B_KV, 36 * KB); }
  __syncwarp();
  if (lane < 12) {
    fence_async_all();
    bulk_g2s(sb + (ty == 0 ? SM_Q : (ty - 1) * 12 * KB) + pc * 3 * KB, img + (ty == 0 ? quarter : (head & 3)) * 24 * KB, 3 * KB, bar + 8 * B_KV);
  }
  __syncwarp();
  poll_all(g_cnt + C_QA + (head + 32 * lane) * 8, ep * 16, lane < 3);
  if (lane == 0) TS(22);
#pragma unroll 1
  for (int i = 1; i < 8; i++) {
    const uint32_t f = bar + 8 * (B_KV + i);
    if (i == 5) mbar_wait(bar + 8 * B_SDONE);
    if (lane == 0) mbar_expect(f, i == 7 ? 36 * KB : 24 * KB);
    __syncwarp();
    if (lane < 12 && (ty || i == 7)) {
      fence_async_all();
      bulk_g2s(sb + (ty == 0 ? SM_Q + 12 * KB : i * 24 * KB + (ty - 1) * 12 * KB) + pc * 3 * KB,
               img + (ty == 0 ? quarter : ((head + i) & 3)) * 24 * KB + (i >> 2) * 3 * KB, 3 * KB, f);
    }
    __syncwarp();
  }
  {
    const float k0 = ldcg_f(g_nrm + (32 + head) * 64 + lane), k1 = ldcg_f(g_nrm + (32 + head) * 64 + 32 + lane);
    const float v0 = ldcg_f(g_nrm + (64 + head) * 64 + lane), v1 = ldcg_f(g_nrm + (64 + head) * 64 + 32 + lane);
    const float qn = ldcg_f(g_nrm + head * 64 + quarter * 16 + (lane & 15));
    const float km = __uint_as_float(__reduce_max_sync(~0u, max(__float_as_uint(k0), __float_as_uint(k1))));
    const float vm = __uint_as_float(__reduce_max_sync(~0u, max(__float_as_uint(v0), __float_as_uint(v1))));
    const bool safe = (qn * km <= 4096.f) && (vm <= 1e24f);
    const uint32_t sm = __ballot_sync(~0u, safe);
    if (lane < 8) sts32(sb + SM_UNS + lane * 4, ((sm >> (2 * lane)) & 3) != 3);
    __syncwarp();
    if (lane == 0) mbar_arrive(bar + 8 * B_UNS);
  }
  poll_all(g_cnt + C_W, ep * 384, lane == 0);
  __syncwarp();
#pragma unroll 1
  for (int i = lane; i < 192; i += 32) {
    float c = 0.f;
#pragma unroll
    for (int u = 0; u < 8; u++) c += ldcg_f(g_cs1 + u * 1536 + j * 192 + i);
    sts32(sb + SM_CS1 + i * 4, __float_as_uint(c));
    sts32(sb + SM_B1 + i * 4, __float_as_uint(__bfloat162float(p.b1[j * 192 + i])));
    if (i < 80) sts32(sb + SM_B2 + i * 4, __float_as_uint(__bfloat162float(p.b2[j * 80 + i])));
  }
  __syncwarp();
  if (lane == 0) {
    const uint8_t* w1 = g_W1 + j * 245760;
    const uint8_t* w2 = g_W2 + j * 245760;
    mbar_wait(bar + 8 * B_KVF);
    fence_async_all();
    mbar_expect(bar + 8 * B_WO, 100 * KB);
#pragma unroll 1
    for (int i = 0; i < 5; i++) bulk_g2s(sb + i * 20 * KB, g_Wo + j * 102400 + i * 20 * KB, 20 * KB, bar + 8 * B_WO);
#pragma unroll 1
    for (int i = 0; i < 8; i++) {
      if (i < 4) mbar_wait(bar + 8 * (B_D3 + (i == 0 ? 3 : i == 1 ? 10 + 2 : i == 2 ? 10 + 6 : 10 + 9)));
      else { mbar_wait(bar + 8 * (B_D4 + i - 4)); mbar_wait(bar + 8 * (B_D4 + 8 + i - 4)); }
      if (i == 1) mbar_wait(bar + 8 * (B_D3 + 9));
      const uint32_t f = bar + 8 * (B_F4B + i);
      mbar_expect(f, 30 * KB);
      bulk_g2s(sb + b4_slot(i), w1 + slice_of(j, i) * 30 * KB, 30 * KB, f);
    }
#pragma unroll 1
    for (int i = 0; i < 24; i++) {
      if (i >= 10) { mbar_wait(bar + 8 * (B_D5 + i - 10)); mbar_wait(bar + 8 * (B_D5 + 24 + i - 10)); }
      else if (i == 1 || i == 4 || i == 7) {
        const int d = i == 1 ? 4 : i == 4 ? 6 : 7;
        mbar_wait(bar + 8 * (B_D4 + d)); mbar_wait(bar + 8 * (B_D4 + 8 + d));
      }
      const uint32_t f = bar + 8 * (B_F5B + i);
      mbar_expect(f, 10 * KB);
      bulk_g2s(sb + b5_slot(i), XB ? g_W2 + i * 10 * KB : w2 + (slice_of(j, i / 3) * 3 + i % 3) * 10 * KB, 10 * KB, f);
    }
  }
}

__device__ __forceinline__ void qkv_stores(uint32_t sb, int rb, int j) {
  const int lane = threadIdx.x & 31;
  const uint32_t bar = sb + SM_BAR;
  const int hl = lane >> 1, hf = lane & 1, gh = half_gh(j, hl >= 6) + (hl >= 6 ? hl - 6 : hl);
  const bool act = lane < 24, early = act && hf == 0 && (gh < 32 || (gh & 3) == (rb >> 2));
  uint8_t* dst = g_img + (size_t)gh * HEADB + rb * 6144 + hf * 3072;
  const uint32_t src = sb + SM_STG + lane * 3072;
  mbar_wait(bar + 8 * B_STG1);
  if (early) { bulk_s2g(dst, src, 3072); bulk_commit(); bulk_wait0(); red_release(g_cnt + C_Q0 + gh * 8 + (rb >> 2)); }
  __syncwarp();
  if (lane == 0) TS(16);
  mbar_wait(bar + 8 * (B_STG1 + 1));
  if (act && !early) { bulk_s2g(dst, src, 3072); bulk_commit(); }
  mbar_wait(bar + 8 * B_NRM1);
  bulk_wait0();
  __syncwarp();
  if (lane == 0) mbar_arrive(bar + 8 * B_SDONE);
  if (act && hf == 0) red_release(g_cnt + C_QA + gh * 8);
  __syncwarp();
}

__device__ __forceinline__ void warp_acts(uint32_t sb, uint32_t ep, int m, int rb, int j, bool last_writer) {
  const int lane = threadIdx.x & 31;
  const uint32_t bar = sb + SM_BAR;
  const int rh = rb * 2 + m;
  poll_all(g_cnt + C_O + rh * 32, ep * 32, lane == 0);
  if (lane == 0) {
    if (m) TS(19);
    fence_async_all();
#pragma unroll 1
    for (int kc = 0; kc < 10; kc++) {
      if (m == 0) { if (kc == 0 || kc == 2 || kc == 5 || kc == 8) mbar_wait(bar + 8 * (B_KVF + (kc + 1) / 3)); }
      else if (kc == 0) mbar_wait(bar + 8 * (B_D3 + 9));
      else if (kc >= 8) mbar_wait(bar + 8 * (B_D3 + 10 + kc - 8));
      const uint32_t f = bar + 8 * (B_F3 + m * 10 + kc);
      mbar_expect(f, 8 * KB);
      bulk_g2s(sb + a3_slot(m, kc), g_O + rh * 81920 + kc * 8 * KB, 8 * KB, f);
    }
    mbar_wait(bar + 8 * (B_HOWN + m));
    bulk_s2g(g_H + rh * 81920 + j * 10 * KB, sb + SM_HOWN + m * 10 * KB, 10 * KB);
    bulk_commit();
    bulk_wait0();
    red_release(g_cnt + C_H + rh * 32 + j);
    if (m) TS(20); else TS(18);
    mbar_wait(bar + 8 * (B_D3 + 10 + (m ? 9 : 7)));
  }
  __syncwarp();
  uint32_t mask = 0;
#pragma unroll 1
  for (int i = 1; i < 8; i++) {
    const int s = slice_of(j, i);
    mask = poll_mask(g_cnt + C_H + rh * 32, ep, lane, mask, s);
    if (lane == 0) {
      fence_async_all();
      if (i >= 4) mbar_wait(bar + 8 * (B_D4 + m * 8 + i - 3));
      const uint32_t f = bar + 8 * (B_F4A + m * 8 + i);
      mbar_expect(f, 10 * KB);
      bulk_g2s(sb + a4_slot(m, i), g_H + rh * 81920 + s * 10 * KB, 10 * KB, f);
    }
    __syncwarp();
  }
  if (lane == 0) {
    mbar_wait(bar + 8 * (B_GOWN + m));
    bulk_s2g(g_G + rh * 196608 + j * 24 * KB, sb + a5_slot(m, 0), 24 * KB);
    bulk_commit();
    bulk_wait0();
    red_release(g_cnt + C_G + rh * 32 + j);
    if (m) TS(21); else TS(29);
  }
  __syncwarp();
  mask = 0;
#pragma unroll 1
  for (int i = 3; i < 24; i++) {
    const int s = slice_of(j, i / 3);
    mask = poll_mask(g_cnt + C_G + rh * 32, ep, lane, mask, s);
    if (lane == 0) {
      fence_async_all();
      if (i >= 6) mbar_wait(bar + 8 * (B_D5 + m * 24 + i - 6));
      else if (i == 4) { mbar_wait(bar + 8 * (B_D4 + 5)); mbar_wait(bar + 8 * (B_D4 + 8 + 5)); }
      const uint32_t f = bar + 8 * (B_F5A + m * 24 + i);
      mbar_expect(f, 8 * KB);
      bulk_g2s(sb + a5_slot(m, i), g_G + (XA ? m * 196608 + i * 8 * KB : rh * 196608 + (s * 3 + i % 3) * 8 * KB), 8 * KB, f);
    }
    __syncwarp();
  }
  if (last_writer && lane == 0) g_cnt[C_EPOCH] = ep;
}

__device__ __forceinline__ void qk_tile(float (&s)[32], const uint32_t (&q)[7], uint32_t a) {
  wgmma_rs_n64_tb0_z<H384>(s, q[0], q[1], q[2], q[3], a + (8 << 16));
  wgmma_rs_n64_tb0_a<H384>(s, q[4], q[5], q[6], q[6], a + 16);
}
__device__ __forceinline__ void pv_tile(float (&o)[12], const uint32_t (&pp)[16], uint32_t a) {
#pragma unroll
  for (int k = 0; k < 4; k++) wgmma_rs_n24_tb1_a<H128>(o, pp[4 * k], pp[4 * k + 1], pp[4 * k + 2], pp[4 * k + 3], a + 768 + k * 48 + (24 << 16));
}

__device__ __forceinline__ void attn_safe(float (&o_out)[12], uint32_t qa, uint32_t sb, int r) {
  const uint32_t bar = sb + SM_BAR;
  const int lane = threadIdx.x & 31;
  uint32_t q[7];
  q[0] = lds32(qa); q[1] = lds32(qa + 384); q[2] = lds32(qa + 128); q[3] = lds32(qa + 512); q[4] = lds32(qa + 256); q[5] = lds32(qa + 640);
  q[6] = 0;
  if ((lane & 3) >= 2) q[4] = q[5] = 0;
  float s[32], o[12];
  zero_acc(o);
  float m0 = -INFINITY, m1 = -INFINITY;
#pragma unroll 1
  for (int jj = 0; jj < 32; jj++) {
    const uint32_t off = dlo(sb, 0) + (jj >> 2) * 1536 + (jj & 3) * 192;
    mbar_wait(bar + 8 * (B_KV + (jj >> 2)));
    if (r == 1 && jj >= 20 && (jj & 3) == 0 && lane == 0) mbar_arrive(bar + 8 * (B_KVF + (jj >> 2) - 5));
#pragma unroll
    for (int i = 0; i < 7; i++) asm volatile("" : "+r"(q[i])::"memory");
    wfence();
    qk_tile(s, q, off);
    wcommit();
    wwait<0>();
    float a0 = m0, a1 = m1;
#pragma unroll
    for (int i = 0; i < 8; i++) { a0 = fmaxf(a0, fmaxf(s[4 * i], s[4 * i + 1])); a1 = fmaxf(a1, fmaxf(s[4 * i + 2], s[4 * i + 3])); }
    a0 = fmaxf(a0, __shfl_xor_sync(~0u, a0, 1)); a0 = fmaxf(a0, __shfl_xor_sync(~0u, a0, 2));
    a1 = fmaxf(a1, __shfl_xor_sync(~0u, a1, 1)); a1 = fmaxf(a1, __shfl_xor_sync(~0u, a1, 2));
    const float c0 = ex2(m0 - a0), c1 = ex2(m1 - a1);
    m0 = a0; m1 = a1;
    uint32_t pp[16];
#pragma unroll
    for (int i = 0; i < 8; i++) {
      const uint32_t sg = ((POLY >> i) & 1) ? 0x80008000u : 0u;
      pp[2 * i] = packbf(ex2(s[4 * i] - m0), ex2(s[4 * i + 1] - m0)) ^ sg;
      pp[2 * i + 1] = packbf(ex2(s[4 * i + 2] - m1), ex2(s[4 * i + 3] - m1)) ^ sg;
    }
#pragma unroll
    for (int i = 0; i < 3; i++) { o[4 * i] *= c0; o[4 * i + 1] *= c0; o[4 * i + 2] *= c1; o[4 * i + 3] *= c1; }
#pragma unroll
    for (int i = 0; i < 12; i++) asm volatile("" : "+f"(o[i])::"memory");
    wfence();
    pv_tile(o, pp, off);
    wcommit();
    wwait<0>();
  }
#pragma unroll
  for (int i = 0; i < 12; i++) asm volatile("mov.b32 %0, %1;" : "=f"(o_out[i]) : "f"(o[i]) : "memory");
}

__global__ void __cluster_dims__(2, 1, 1) __launch_bounds__(640, 1)
block_kernel(const __grid_constant__ CUtensorMap tmx, const __grid_constant__ CUtensorMap tmw, const Params p) {
  extern __shared__ __align__(1024) uint8_t smem[];
  const uint32_t sb = (uint32_t)__cvta_generic_to_shared(smem);
  const uint32_t bar = sb + SM_BAR;
  const int rank = blockIdx.x & 1, cl = blockIdx.x >> 1, tp = cl - 4;
  const int grp = cl < 4 ? 0 : tp < 32 ? (tp & 7) : 1 + (tp - 32) % 7;
  const int j = cl < 4 ? 4 + cl : tp < 32 ? (tp >> 3) : 4 + (tp - 32) / 7;
  const int rb = grp * 2 + rank;
  const int head = grp * 4 + (j >> 1), quarter = (j & 1) * 2 + rank;
  if (threadIdx.x == 0) { TS(0); TSG(30); }
  const int warp = __shfl_sync(~0u, threadIdx.x >> 5, 0), lane = threadIdx.x & 31;

  if (warp >= 16) {
    asm volatile("setmaxnreg.dec.sync.aligned.u32 32;");
    if (warp == 16) {
      if (sb & 1023) __trap();
      if (lane == 0) {
#pragma unroll
        for (int kc = 0; kc < 4; kc++) mbar_init(bar + 8 * (B_F1 + kc), 1);
        fence_async_smem();
      }
      __syncwarp();
      bar_arrive(0, 640);
      if (lane == 0) {
#pragma unroll 1
        for (int kc = 0; kc < 4; kc++) load_stage1(&tmx, &tmw, sb, kc, rb, j);
        TS(23);
      }
      __syncwarp();
      bar_sync(7, 544);
      warp_weights(&tmx, &tmw, p, sb, rb, j, head, quarter);
    } else {
      const uint32_t ep = ld_acquire(g_cnt + C_EPOCH) + 1;
      bar_sync(0, 640);
      if (warp == 17) qkv_stores(sb, rb, j);
      helper_warp(p, blockIdx.x * 3 + warp - 17, bar);
      if (warp < 19) warp_acts(sb, ep, warp - 17, rb, j, blockIdx.x == 0 && warp == 18);
    }
    return;
  }

  asm volatile("setmaxnreg.inc.sync.aligned.u32 112;");
  const int wg = warp >> 2, w = warp & 3, g = lane >> 2, t = lane & 3;
  const int mh = wg & 1, nh = wg >> 1;
  {
    if (lane == 0) {
#pragma unroll 1
      for (int i = 4 + warp; i < B_END; i += 16) mbar_init(bar + 8 * i, i < B_C4 ? 1 : i < B_C8 ? 4 : i < B_C16 ? 8 : 16);
      fence_async_smem();
    }
    __syncwarp();
    bar_arrive(7, 544);
    uint2 xr[5];
    const uint2* xp = (const uint2*)(p.x + (size_t)(rb * 128 + j * 16 + warp) * 640);
#pragma unroll
    for (int i = 0; i < 5; i++) xr[i] = __ldg(xp + i * 32 + lane);
    uint4 wr[3];
    const uint4* wp = (const uint4*)(p.wqkv + (size_t)(rb * 40 + warp) * 1920 + j * 120) + (lane < 15 ? lane : lane < 30 ? lane + 105 : 0);
    wr[0] = __ldg(wp); wr[1] = __ldg(wp + 16 * 240);
    wr[2] = warp < 8 ? __ldg(wp + 32 * 240) : make_uint4(0, 0, 0, 0);
    bar_sync(0, 640);
    if (threadIdx.x == 0) TS(25);

    float acc[60];
    zero_acc(acc);
    const uint32_t dA = dlo(sb + mh * 8 * KB, 16), dB = dlo(sb + 16 * KB + nh * 16 * KB, 8 * KB);
#pragma unroll 1
    for (int kc = 0; kc < 10; kc++) {
      const int so = (kc & 3) * (48 * KB / 16);
      mbar_wait(bar + 8 * (B_F1 + kc));
      if (kc == 0 && threadIdx.x == 0) TS(1);
      if (threadIdx.x == 0) TS(32 + kc);
      wfence();
#pragma unroll
      for (int k = 0; k < 4; k++) wgmma_ss_n120_tb1_a<HSW, HSW>(acc, dA + so + k * 2, dB + so + k * 128);
      wcommit();
      if (kc == 0) {
        float s = 0.f;
#pragma unroll
        for (int i = 0; i < 5; i++) s += (bflo(xr[i].x) + bfhi(xr[i].x)) + (bflo(xr[i].y) + bfhi(xr[i].y));
#pragma unroll
        for (int o = 16; o; o >>= 1) s += __shfl_xor_sync(~0u, s, o);
        const float mean = s * (1.f / 640.f);
        float v = 0.f;
#pragma unroll
        for (int i = 0; i < 5; i++) {
          const float a = bflo(xr[i].x) - mean, b = bfhi(xr[i].x) - mean, c = bflo(xr[i].y) - mean, d = bfhi(xr[i].y) - mean;
          v += (a * a + b * b) + (c * c + d * d);
        }
#pragma unroll
        for (int o = 16; o; o >>= 1) v += __shfl_xor_sync(~0u, v, o);
        if (lane == 0) g_st1[rb * 128 + j * 16 + warp] = make_float2(mean, rsqrtf(v * (1.f / 640.f) + 1e-5f));
        if (lane < 30) {
          const uint32_t a = sb + SM_RED + warp * 960 + lane * 32;
          sts128f(a, make_float4(bflo(wr[0].x) + bflo(wr[1].x) + bflo(wr[2].x), bfhi(wr[0].x) + bfhi(wr[1].x) + bfhi(wr[2].x),
                                 bflo(wr[0].y) + bflo(wr[1].y) + bflo(wr[2].y), bfhi(wr[0].y) + bfhi(wr[1].y) + bfhi(wr[2].y)));
          sts128f(a + 16, make_float4(bflo(wr[0].z) + bflo(wr[1].z) + bflo(wr[2].z), bfhi(wr[0].z) + bfhi(wr[1].z) + bfhi(wr[2].z),
                                      bflo(wr[0].w) + bflo(wr[1].w) + bflo(wr[2].w), bfhi(wr[0].w) + bfhi(wr[1].w) + bfhi(wr[2].w)));
        }
        bar_sync(1, 512);
        if (threadIdx.x < 240) {
          float c = 0.f;
#pragma unroll
          for (int i = 0; i < 16; i++) c += __uint_as_float(lds32(sb + SM_RED + i * 960 + threadIdx.x * 4));
          g_csq[(j * 16 + rb) * 240 + threadIdx.x] = c;
        }
        bar_sync(1, 512);
        if (threadIdx.x == 511) red_release(g_cnt + C_A);
      } else {
        wwait<1>();
        if (lane == 0) mbar_arrive(bar + 8 * (B_D1 + kc - 1));
      }
    }
    wwait<0>();
#pragma unroll
    for (int i = 0; i < 60; i++) asm volatile("" : "+f"(acc[i])::"memory");
    if (lane == 0) mbar_arrive(bar + 8 * (B_D1 + 9));
    if (threadIdx.x == 0) TS(2);
    mbar_wait(bar + 8 * (B_D1 + 7));
    mbar_wait(bar + 8 * B_AUX1);
    const float2 st0 = lds64f(sb + SM_ST1 + (mh * 64 + w * 16 + g) * 8), st1 = lds64f(sb + SM_ST1 + (mh * 64 + w * 16 + g + 8) * 8);
    const uint32_t stg = sb + SM_STG + nh * 6 * 6144 + mh * 3072;
    const uint32_t rowa = stg + 2 * w * 384 + g * 16;
    const uint32_t off[5] = {(uint32_t)t * 4, 128u + t * 4, t < 2 ? 256u + t * 4 : 6144u + (t - 2) * 4,
                             t < 2 ? 6144u + 8 + t * 4 : 6144u + 128 + (t - 2) * 4, t < 2 ? 6144u + 136 + t * 4 : 6144u + 256 + (t - 2) * 4};
    const int prow = threadIdx.x & 63, ph = (threadIdx.x >> 6) & 1;
    const uint32_t pada = stg + ph * 6144 + (prow >> 3) * 384 + (prow & 7) * 16;
    const bool ppoly = (POLY >> (prow >> 3)) & 1;
#pragma unroll
    for (int pr = 0; pr < 3; pr++) {
      const int type = (half_gh(j, nh) + pr * 2) >> 5;
      float m0 = st0.y, m1 = st1.y;
      if (type == 0) { m0 *= 0.32259784f; m1 *= 0.32259784f; }
      if (type == 2) { if ((POLY >> (2 * w)) & 1) m0 = -m0; if ((POLY >> (2 * w + 1)) & 1) m1 = -m1; }
#pragma unroll
      for (int r = 0; r < 5; r++) {
        const int nb = pr * 5 + r;
        const float2 c = lds64f(sb + SM_CSQ + (nh * 120 + nb * 8 + t * 2) * 4);
        sts32(rowa + pr * 12288 + off[r], packbf(fmaf(-st0.x, c.x, acc[4 * nb]) * m0, fmaf(-st0.x, c.y, acc[4 * nb + 1]) * m0));
        sts32(rowa + pr * 12288 + off[r] + 384, packbf(fmaf(-st1.x, c.x, acc[4 * nb + 2]) * m1, fmaf(-st1.x, c.y, acc[4 * nb + 3]) * m1));
      }
      uint32_t p0, p1;
      if (type == 0) { p0 = 0x42FD4380u; p1 = 0x0000BDB4u; }
      else if (type == 1) { p0 = ppoly ? 0x3F803F80u : 0u; p1 = ppoly ? 0x00003F80u : 0u; }
      else { p0 = ppoly ? 0x0000BF80u : 0x00003F80u; p1 = 0u; }
      sts64(pada + pr * 12288 + 264, p0, p1);
    }
    fence_async_smem();
    __syncwarp();
    if (lane == 0) mbar_arrive(bar + 8 * (B_STG1 + mh));
    bar_sync(2 + wg, 128);
#pragma unroll
    for (int pr = 0; pr < 3; pr++) {
      const uint4 a = lds128(pada + pr * 12288), b = lds128(pada + pr * 12288 + 128);
      const uint2 c = lds64(pada + pr * 12288 + 256);
      const float n = sq2(a.x, sq2(a.y, sq2(a.z, sq2(a.w, sq2(c.x, 0.f))))) + sq2(b.x, sq2(b.y, sq2(b.z, sq2(b.w, sq2(c.y, 0.f)))));
      const uint32_t mx = __reduce_max_sync(~0u, __float_as_uint(n));
      if (lane == 0) g_nrm[(half_gh(j, nh) + pr * 2 + ph) * 64 + rb * 4 + mh * 2 + (w & 1)] = __uint_as_float(mx);
    }
    if (lane == 0) mbar_arrive(bar + 8 * B_NRM1);
    if (threadIdx.x == 0) TS(3);
  }
  {
    mbar_wait(bar + 8 * B_KV);
    if (threadIdx.x == 0) TS(4);
#pragma unroll 1
    for (int r = 0; r < 2; r++) {
      const uint32_t qa = sb + SM_Q + r * 12 * KB + wg * 3 * KB + 2 * w * 384 + g * 16 + t * 4;
      float o[12];
      bool unsafe = r == 1 && __any_sync(~0u, lds32(sb + SM_UNS + (2 * wg + 1) * 4));
      if (!unsafe) {
        uint32_t q[7];
        q[0] = lds32(qa); q[1] = lds32(qa + 384); q[2] = lds32(qa + 128); q[3] = lds32(qa + 512); q[4] = lds32(qa + 256); q[5] = lds32(qa + 640);
        q[6] = 0;
        zero_acc(o);
#pragma unroll
        for (int i = 0; i < 7; i++) asm volatile("" : "+r"(q[i])::"memory");
        float s[32];
        uint32_t pp[16];
        wfence();
        qk_tile(s, q, dlo(sb, 0));
        wcommit();
#pragma unroll 1
        for (int jp = 0; jp < 16; jp++) {
          const uint32_t off0 = dlo(sb, 0) + (jp >> 1) * 1536 + (jp & 1) * 384;
          const uint32_t offn = jp == 15 ? off0 : off0 + ((jp & 1) ? 1152 : 384);
#pragma unroll
          for (int h = 0; h < 2; h++) {
            wwait<0>();
            if (h == 0 && r == 1 && jp >= 10 && !(jp & 1) && lane == 0) mbar_arrive(bar + 8 * (B_KVF - 5 + (jp >> 1)));
#pragma unroll
            for (int i = 0; i < 8; i++) {
              if ((POLY >> i) & 1) {
                pp[2 * i] = exp2_pair(s[4 * i], s[4 * i + 1]); pp[2 * i + 1] = exp2_pair(s[4 * i + 2], s[4 * i + 3]);
              } else {
                pp[2 * i] = packbf(ex2(s[4 * i]), ex2(s[4 * i + 1])); pp[2 * i + 1] = packbf(ex2(s[4 * i + 2]), ex2(s[4 * i + 3]));
              }
            }
            if (h == 1 && (jp & 1) && jp < 15) mbar_wait(bar + 8 * (B_KV + ((jp + 1) >> 1)));
            wfence();
            pv_tile(o, pp, off0 + h * 192);
            qk_tile(s, q, h == 0 ? off0 + 192 : offn);
            wcommit();
          }
        }
        wwait<0>();
#pragma unroll
        for (int i = 0; i < 12; i++) asm volatile("" : "+f"(o[i])::"memory");
      }
      if (r == 0) {
        mbar_wait(bar + 8 * B_UNS);
        unsafe = __any_sync(~0u, lds32(sb + SM_UNS + 2 * wg * 4));
      }
      if (unsafe) attn_safe(o, qa, sb, r);
      if (r == 1 && lane == 0) mbar_arrive(bar + 8 * (B_KVF + 3));
      const float i0 = rcp(__shfl_sync(~0u, o[8], (lane & ~3) | 2)), i1 = rcp(__shfl_sync(~0u, o[10], (lane & ~3) | 2));
      const int orh = (quarter * 4 + wg) * 2 + r;
      uint8_t* op = g_O + orh * 81920 + (head >> 1) * 5 * KB + (w * 16 + g) * 16 + t * 4;
      uint8_t* oa = op + (head & 1) * 2 * KB;
      *(uint32_t*)(oa) = packbf(o[0] * i0, o[1] * i0);
      *(uint32_t*)(oa + 128) = packbf(o[2] * i1, o[3] * i1);
      *(uint32_t*)(oa + KB) = packbf(o[4] * i0, o[5] * i0);
      *(uint32_t*)(oa + KB + 128) = packbf(o[6] * i1, o[7] * i1);
      if (t < 2) {
        *(uint32_t*)(op + 4 * KB + (head & 1) * 8) = packbf(o[8] * i0, o[9] * i0);
        *(uint32_t*)(op + 4 * KB + (head & 1) * 8 + 128) = packbf(o[10] * i1, o[11] * i1);
      }
      bar_sync(2 + wg, 128);
      if (wg == 0 ? threadIdx.x == 127 : (threadIdx.x & 127) == 96) red_release(g_cnt + C_O + orh * 32);
      if (threadIdx.x == 0) TS(5 + r);
    }
  }
  const int rowl = mh * 64 + w * 16;
  const uint32_t stm = (lane >> 4) * KB + (w * 16 + (lane & 15)) * 16;
  const uint32_t hown = sb + SM_HOWN + mh * 10 * KB;
  if (nh == 0) {
    uint32_t xr[20];
    const uint32_t* xp = (const uint32_t*)(p.x + (size_t)(rb * 128 + rowl + g) * 640 + j * 80) + t;
#pragma unroll
    for (int i = 0; i < 10; i++) { xr[2 * i] = __ldg(xp + i * 4); xr[2 * i + 1] = __ldg(xp + i * 4 + 8 * 320); }
    float acc[40];
    zero_acc(acc);
    const uint32_t dA = dlo(sb, KB), dB = dlo(sb, 1280);
    mbar_wait(bar + 8 * B_WO);
#pragma unroll 1
    for (int kc = 0; kc < 10; kc++) {
      const int ao = a3_slot(mh, kc) >> 4, bo = kc * 640;
      mbar_wait(bar + 8 * (B_F3 + mh * 10 + kc));
      if (kc == 0 && threadIdx.x == 128) TS(7);
      wfence();
#pragma unroll
      for (int k = 0; k < 4; k++) wgmma_ss_n80_tb1_a<H128, H128>(acc, dA + ao + k * 128, dB + bo + k * 160);
      wcommit();
      if (kc) { wwait<1>(); if (lane == 0) mbar_arrive(bar + 8 * (B_D3 + mh * 10 + kc - 1)); }
    }
    wwait<0>();
#pragma unroll
    for (int i = 0; i < 40; i++) asm volatile("" : "+f"(acc[i])::"memory");
    if (lane == 0) mbar_arrive(bar + 8 * (B_D3 + mh * 10 + 9));
    if (threadIdx.x == 128) TS(8);
    if (threadIdx.x == 0) TS(26);
    float s0 = 0.f, s1 = 0.f;
#pragma unroll
    for (int i = 0; i < 10; i++) {
      xr[2 * i] = packbf(acc[4 * i] + bflo(xr[2 * i]), acc[4 * i + 1] + bfhi(xr[2 * i]));
      xr[2 * i + 1] = packbf(acc[4 * i + 2] + bflo(xr[2 * i + 1]), acc[4 * i + 3] + bfhi(xr[2 * i + 1]));
      s0 += bflo(xr[2 * i]) + bfhi(xr[2 * i]); s1 += bflo(xr[2 * i + 1]) + bfhi(xr[2 * i + 1]);
    }
#pragma unroll
    for (int i = 0; i < 5; i++) stsm4(hown + i * 2 * KB + stm, xr[4 * i], xr[4 * i + 1], xr[4 * i + 2], xr[4 * i + 3]);
    fence_async_smem();
    s0 = qsum(s0) * (1.f / 80.f); s1 = qsum(s1) * (1.f / 80.f);
    float v0 = 0.f, v1 = 0.f;
#pragma unroll
    for (int i = 0; i < 10; i++) {
      const float a = bflo(xr[2 * i]) - s0, b = bfhi(xr[2 * i]) - s0, c = bflo(xr[2 * i + 1]) - s1, d = bfhi(xr[2 * i + 1]) - s1;
      v0 += a * a + b * b; v1 += c * c + d * d;
    }
    v0 = qsum(v0); v1 = qsum(v1);
    if (t < 2) g_st2[(rb * 8 + j) * 128 + rowl + g + t * 8] = t ? make_float2(s1, v1) : make_float2(s0, v0);
    __syncwarp();
    if (lane == 0) mbar_arrive(bar + 8 * (B_HOWN + mh));
    if (threadIdx.x == 128) TS(9);
  }
  {
    float acc[48];
    zero_acc(acc);
    const uint32_t dA = dlo(sb, KB), dB = dlo(sb + nh * 1536, 3072);
    float2 pa, pb, pc, pd;
    mbar_wait(bar + 8 * B_WO);
#pragma unroll 1
    for (int i = 0; i < 8; i++) {
      const int ao = (i == 0 ? SM_HOWN + mh * 10 * KB : a4_slot(mh, i)) >> 4, bo = b4_slot(i) >> 4;
      mbar_wait(bar + 8 * (i == 0 ? B_HOWN + mh : B_F4A + mh * 8 + i));
      mbar_wait(bar + 8 * (B_F4B + i));
      if (i == 1 && threadIdx.x == 128) TS(10);
      if (i == 1 && threadIdx.x == 0) TS(27);
      if (i == 7) {
        const float2* sp = g_st2 + (rb * 8 + 2 * t) * 128 + rowl + g;
        pa = ldcg_f2(sp); pb = ldcg_f2(sp + 128); pc = ldcg_f2(sp + 8); pd = ldcg_f2(sp + 136);
      }
      wfence();
#pragma unroll
      for (int k = 0; k < 5; k++) wgmma_ss_n96_tb1_a<H128, H128>(acc, dA + ao + k * 128, dB + bo + k * 384);
      wcommit();
      if (i == 0) wwait<0>(); else wwait<1>();
      if (i != 1 && lane == 0) mbar_arrive(bar + 8 * (B_D4 + mh * 8 + (i ? i - 1 : 0)));
    }
    const float mean0 = qsum(pa.x + pb.x) * 0.125f, mean1 = qsum(pc.x + pd.x) * 0.125f;
    const float e0 = pa.x - mean0, e1 = pb.x - mean0, e2 = pc.x - mean1, e3 = pd.x - mean1;
    const float r0 = rsqrtf(qsum(pa.y + pb.y + 80.f * (e0 * e0 + e1 * e1)) * (1.f / 640.f) + 1e-5f);
    const float r1 = rsqrtf(qsum(pc.y + pd.y + 80.f * (e2 * e2 + e3 * e3)) * (1.f / 640.f) + 1e-5f);
    wwait<0>();
#pragma unroll
    for (int i = 0; i < 48; i++) asm volatile("" : "+f"(acc[i])::"memory");
    if (lane == 0) mbar_arrive(bar + 8 * (B_D4 + mh * 8 + 7));
    if (threadIdx.x == 128) TS(11);
    if (threadIdx.x == 0) TS(24);
    uint32_t gq[24];
#pragma unroll
    for (int i = 0; i < 12; i++) {
      const float2 c = lds64f(sb + SM_CS1 + (nh * 96 + i * 8 + t * 2) * 4), b = lds64f(sb + SM_B1 + (nh * 96 + i * 8 + t * 2) * 4);
      const float a0 = fmaxf(fmaf(fmaf(-mean0, c.x, acc[4 * i]), r0, b.x), 0.f), a1 = fmaxf(fmaf(fmaf(-mean0, c.y, acc[4 * i + 1]), r0, b.y), 0.f);
      const float a2 = fmaxf(fmaf(fmaf(-mean1, c.x, acc[4 * i + 2]), r1, b.x), 0.f), a3 = fmaxf(fmaf(fmaf(-mean1, c.y, acc[4 * i + 3]), r1, b.y), 0.f);
      gq[2 * i] = packbf(a0 * a0, a1 * a1); gq[2 * i + 1] = packbf(a2 * a2, a3 * a3);
    }
    mbar_wait(bar + 8 * (B_D4 + mh * 8 + 7));
#pragma unroll
    for (int i = 0; i < 6; i++) stsm4(sb + a5_slot(mh, 0) + (nh * 6 + i) * 2 * KB + stm, gq[4 * i], gq[4 * i + 1], gq[4 * i + 2], gq[4 * i + 3]);
    fence_async_smem();
    __syncwarp();
    if (lane == 0) mbar_arrive(bar + 8 * (B_GOWN + mh));
    if (threadIdx.x == 128) TS(12);
  }
  if (nh == 0) {
    float acc[40];
    zero_acc(acc);
    const uint32_t dA = dlo(sb, KB), dB = dlo(sb, 1280);
#pragma unroll 1
    for (int i = 0; i < 24; i++) {
      const int ao = a5_slot(mh, i) >> 4, bo = b5_slot(i) >> 4;
      if (!(XW & 1) || i < 4 || i == 23) mbar_wait(bar + 8 * (i < 3 ? B_GOWN + mh : B_F5A + mh * 24 + i));
      if (!(XW & 2) || i < 4 || i == 23) mbar_wait(bar + 8 * (B_F5B + i));
      if (i == 3 && threadIdx.x == 128) TS(13);
      if (threadIdx.x == 128 && (i & 1)) TS(42 + (i >> 1));
      wfence();
#pragma unroll
      for (int k = 0; k < 4; k++) wgmma_ss_n80_tb1_a<H128, H128>(acc, dA + ao + k * 128, dB + bo + k * 160);
      wcommit();
      if (i == 2) wwait<0>(); else wwait<1>();
      if (i && i != 3 && lane == 0) mbar_arrive(bar + 8 * (B_D5 + mh * 24 + i - 1));
      if (i == 2 && lane == 0) mbar_arrive(bar + 8 * (B_D5 + mh * 24 + 2));
    }
    wwait<0>();
#pragma unroll
    for (int i = 0; i < 40; i++) asm volatile("" : "+f"(acc[i])::"memory");
    if (threadIdx.x == 128) TS(14);
    uint32_t* op = (uint32_t*)(p.out + (size_t)(rb * 128 + rowl + g) * 640 + j * 80) + t;
#pragma unroll
    for (int i = 0; i < 10; i++) {
      const float2 b = lds64f(sb + SM_B2 + (i * 8 + t * 2) * 4);
      const uint32_t h0 = lds32(hown + i * KB + (w * 16 + g) * 16 + t * 4), h1 = lds32(hown + i * KB + (w * 16 + g + 8) * 16 + t * 4);
      op[i * 4] = packbf(acc[4 * i] + b.x + bflo(h0), acc[4 * i + 1] + b.y + bfhi(h0));
      op[i * 4 + 8 * 320] = packbf(acc[4 * i + 2] + b.x + bflo(h1), acc[4 * i + 3] + b.y + bfhi(h1));
    }
    if (threadIdx.x == 128) { TS(15); TSG(31); }
  }
}

typedef CUresult (*EncodeFn)(CUtensorMap*, CUtensorMapDataType, cuuint32_t, void*, const cuuint64_t*, const cuuint64_t*, const cuuint32_t*,
                             const cuuint32_t*, CUtensorMapInterleave, CUtensorMapSwizzle, CUtensorMapL2promotion, CUtensorMapFloatOOBfill);

}

extern "C" void kernel_launch(void* const* d_in, const int* in_sizes, int n_in, void* d_out, int out_size) {
  static EncodeFn enc = nullptr;
  if (!enc) {
    void* fn = nullptr;
    cudaDriverEntryPointQueryResult qr;
    cudaGetDriverEntryPoint("cuTensorMapEncodeTiled", &fn, cudaEnableDefault, &qr);
    enc = (EncodeFn)fn;
    cudaFuncSetAttribute(block_kernel, cudaFuncAttributeMaxDynamicSharedMemorySize, SMEM_BYTES);
  }
  Params p;
  p.x = (const __nv_bfloat16*)d_in[0]; p.wqkv = (const __nv_bfloat16*)d_in[1]; p.wo = (const __nv_bfloat16*)d_in[2];
  p.w1 = (const __nv_bfloat16*)d_in[4]; p.b1 = (const __nv_bfloat16*)d_in[5]; p.w2 = (const __nv_bfloat16*)d_in[6];
  p.b2 = (const __nv_bfloat16*)d_in[7]; p.out = (__nv_bfloat16*)d_out;
  CUtensorMap tmx, tmw;
  const cuuint32_t es[2] = {1, 1};
  {
    const cuuint64_t dim[2] = {640, 2048}, str[1] = {1280};
    const cuuint32_t box[2] = {64, 128};
    enc(&tmx, CU_TENSOR_MAP_DATA_TYPE_BFLOAT16, 2, d_in[0], dim, str, box, es, CU_TENSOR_MAP_INTERLEAVE_NONE, CU_TENSOR_MAP_SWIZZLE_128B,
        CU_TENSOR_MAP_L2_PROMOTION_L2_128B, CU_TENSOR_MAP_FLOAT_OOB_FILL_NONE);
  }
  {
    const cuuint64_t dim[2] = {1920, 640}, str[1] = {3840};
    const cuuint32_t box[2] = {64, 64};
    enc(&tmw, CU_TENSOR_MAP_DATA_TYPE_BFLOAT16, 2, d_in[1], dim, str, box, es, CU_TENSOR_MAP_INTERLEAVE_NONE, CU_TENSOR_MAP_SWIZZLE_128B,
        CU_TENSOR_MAP_L2_PROMOTION_L2_128B, CU_TENSOR_MAP_FLOAT_OOB_FILL_NONE);
  }
  block_kernel<<<128, 640, SMEM_BYTES>>>(tmx, tmw, p);
}
```

```cpp
#include <cuda_runtime.h>
#include <cuda_bf16.h>
#include <cuda.h>
#include <stdint.h>

namespace {

template <uint32_t HB>
__device__ __forceinline__ void wgmma_rs_n128_tb1_a(float (&d)[64], uint32_t a0, uint32_t a1, uint32_t a2, uint32_t a3, uint32_t db) {
  asm volatile("{\n.reg .b64 db;\nmov.b64 db, {%68, %69};\n"
    "wgmma.mma_async.sync.aligned.m64n128k16.f32.bf16.bf16 "
    "{%0, %1, %2, %3, %4, %5, %6, %7, %8, %9, %10, %11, %12, %13, %14, %15, %16, %17, %18, %19, "
    "%20, %21, %22, %23, %24, %25, %26, %27, %28, %29, %30, %31, %32, %33, %34, %35, %36, %37, %38, %39, "
    "%40, %41, %42, %43, %44, %45, %46, %47, %48, %49, %50, %51, %52, %53, %54, %55, %56, %57, %58, %59, "
    "%60, %61, %62, %63}, "
    "{%64,%65,%66,%67}, db, 1, 1, 1, 1;\n}\n"
    : "+f"(d[0]), "+f"(d[1]), "+f"(d[2]), "+f"(d[3]), "+f"(d[4]), "+f"(d[5]), "+f"(d[6]), "+f"(d[7]), "+f"(d[8]), "+f"(d[9]),
      "+f"(d[10]), "+f"(d[11]), "+f"(d[12]), "+f"(d[13]), "+f"(d[14]), "+f"(d[15]), "+f"(d[16]), "+f"(d[17]), "+f"(d[18]), "+f"(d[19]),
      "+f"(d[20]), "+f"(d[21]), "+f"(d[22]), "+f"(d[23]), "+f"(d[24]), "+f"(d[25]), "+f"(d[26]), "+f"(d[27]), "+f"(d[28]), "+f"(d[29]),
      "+f"(d[30]), "+f"(d[31]), "+f"(d[32]), "+f"(d[33]), "+f"(d[34]), "+f"(d[35]), "+f"(d[36]), "+f"(d[37]), "+f"(d[38]), "+f"(d[39]),
      "+f"(d[40]), "+f"(d[41]), "+f"(d[42]), "+f"(d[43]), "+f"(d[44]), "+f"(d[45]), "+f"(d[46]), "+f"(d[47]), "+f"(d[48]), "+f"(d[49]),
      "+f"(d[50]), "+f"(d[51]), "+f"(d[52]), "+f"(d[53]), "+f"(d[54]), "+f"(d[55]), "+f"(d[56]), "+f"(d[57]), "+f"(d[58]), "+f"(d[59]),
      "+f"(d[60]), "+f"(d[61]), "+f"(d[62]), "+f"(d[63])
    : "r"(a0), "r"(a1), "r"(a2), "r"(a3), "r"(db), "n"(HB));
}
template <uint32_t HB>
__device__ __forceinline__ void wgmma_rs_n128_tb1_z(float (&d)[64], uint32_t a0, uint32_t a1, uint32_t a2, uint32_t a3, uint32_t db) {
  asm volatile("{\n.reg .b64 db;\nmov.b64 db, {%68, %69};\n"
    "wgmma.mma_async.sync.aligned.m64n128k16.f32.bf16.bf16 "
    "{%0, %1, %2, %3, %4, %5, %6, %7, %8, %9, %10, %11, %12, %13, %14, %15, %16, %17, %18, %19, "
    "%20, %21, %22, %23, %24, %25, %26, %27, %28, %29, %30, %31, %32, %33, %34, %35, %36, %37, %38, %39, "
    "%40, %41, %42, %43, %44, %45, %46, %47, %48, %49, %50, %51, %52, %53, %54, %55, %56, %57, %58, %59, "
    "%60, %61, %62, %63}, "
    "{%64,%65,%66,%67}, db, 0, 1, 1, 1;\n}\n"
    : "=f"(d[0]), "=f"(d[1]), "=f"(d[2]), "=f"(d[3]), "=f"(d[4]), "=f"(d[5]), "=f"(d[6]), "=f"(d[7]), "=f"(d[8]), "=f"(d[9]),
      "=f"(d[10]), "=f"(d[11]), "=f"(d[12]), "=f"(d[13]), "=f"(d[14]), "=f"(d[15]), "=f"(d[16]), "=f"(d[17]), "=f"(d[18]), "=f"(d[19]),
      "=f"(d[20]), "=f"(d[21]), "=f"(d[22]), "=f"(d[23]), "=f"(d[24]), "=f"(d[25]), "=f"(d[26]), "=f"(d[27]), "=f"(d[28]), "=f"(d[29]),
      "=f"(d[30]), "=f"(d[31]), "=f"(d[32]), "=f"(d[33]), "=f"(d[34]), "=f"(d[35]), "=f"(d[36]), "=f"(d[37]), "=f"(d[38]), "=f"(d[39]),
      "=f"(d[40]), "=f"(d[41]), "=f"(d[42]), "=f"(d[43]), "=f"(d[44]), "=f"(d[45]), "=f"(d[46]), "=f"(d[47]), "=f"(d[48]), "=f"(d[49]),
      "=f"(d[50]), "=f"(d[51]), "=f"(d[52]), "=f"(d[53]), "=f"(d[54]), "=f"(d[55]), "=f"(d[56]), "=f"(d[57]), "=f"(d[58]), "=f"(d[59]),
      "=f"(d[60]), "=f"(d[61]), "=f"(d[62]), "=f"(d[63])
    : "r"(a0), "r"(a1), "r"(a2), "r"(a3), "r"(db), "n"(HB));
}
template <uint32_t HB>
__device__ __forceinline__ void wgmma_rs_n24_tb1_a(float (&d)[12], uint32_t a0, uint32_t a1, uint32_t a2, uint32_t a3, uint32_t db) {
  asm volatile("{\n.reg .b64 db;\nmov.b64 db, {%16, %17};\n"
    "wgmma.mma_async.sync.aligned.m64n24k16.f32.bf16.bf16 "
    "{%0, %1, %2, %3, %4, %5, %6, %7, %8, %9, %10, %11}, "
    "{%12,%13,%14,%15}, db, 1, 1, 1, 1;\n}\n"
    : "+f"(d[0]), "+f"(d[1]), "+f"(d[2]), "+f"(d[3]), "+f"(d[4]), "+f"(d[5]), "+f"(d[6]), "+f"(d[7]), "+f"(d[8]), "+f"(d[9]),
      "+f"(d[10]), "+f"(d[11])
    : "r"(a0), "r"(a1), "r"(a2), "r"(a3), "r"(db), "n"(HB));
}
template <uint32_t HB>
__device__ __forceinline__ void wgmma_rs_n32_tb1_a(float (&d)[16], uint32_t a0, uint32_t a1, uint32_t a2, uint32_t a3, uint32_t db) {
  asm volatile("{\n.reg .b64 db;\nmov.b64 db, {%20, %21};\n"
    "wgmma.mma_async.sync.aligned.m64n32k16.f32.bf16.bf16 "
    "{%0, %1, %2, %3, %4, %5, %6, %7, %8, %9, %10, %11, %12, %13, %14, %15}, "
    "{%16,%17,%18,%19}, db, 1, 1, 1, 1;\n}\n"
    : "+f"(d[0]), "+f"(d[1]), "+f"(d[2]), "+f"(d[3]), "+f"(d[4]), "+f"(d[5]), "+f"(d[6]), "+f"(d[7]), "+f"(d[8]), "+f"(d[9]),
      "+f"(d[10]), "+f"(d[11]), "+f"(d[12]), "+f"(d[13]), "+f"(d[14]), "+f"(d[15])
    : "r"(a0), "r"(a1), "r"(a2), "r"(a3), "r"(db), "n"(HB));
}
template <uint32_t HB>
__device__ __forceinline__ void wgmma_rs_n32_tb1_z(float (&d)[16], uint32_t a0, uint32_t a1, uint32_t a2, uint32_t a3, uint32_t db) {
  asm volatile("{\n.reg .b64 db;\nmov.b64 db, {%20, %21};\n"
    "wgmma.mma_async.sync.aligned.m64n32k16.f32.bf16.bf16 "
    "{%0, %1, %2, %3, %4, %5, %6, %7, %8, %9, %10, %11, %12, %13, %14, %15}, "
    "{%16,%17,%18,%19}, db, 0, 1, 1, 1;\n}\n"
    : "=f"(d[0]), "=f"(d[1]), "=f"(d[2]), "=f"(d[3]), "=f"(d[4]), "=f"(d[5]), "=f"(d[6]), "=f"(d[7]), "=f"(d[8]), "=f"(d[9]),
      "=f"(d[10]), "=f"(d[11]), "=f"(d[12]), "=f"(d[13]), "=f"(d[14]), "=f"(d[15])
    : "r"(a0), "r"(a1), "r"(a2), "r"(a3), "r"(db), "n"(HB));
}
template <uint32_t HB>
__device__ __forceinline__ void wgmma_rs_n48_tb1_a(float (&d)[24], uint32_t a0, uint32_t a1, uint32_t a2, uint32_t a3, uint32_t db) {
  asm volatile("{\n.reg .b64 db;\nmov.b64 db, {%28, %29};\n"
    "wgmma.mma_async.sync.aligned.m64n48k16.f32.bf16.bf16 "
    "{%0, %1, %2, %3, %4, %5, %6, %7, %8, %9, %10, %11, %12, %13, %14, %15, %16, %17, %18, %19, "
    "%20, %21, %22, %23}, "
    "{%24,%25,%26,%27}, db, 1, 1, 1, 1;\n}\n"
    : "+f"(d[0]), "+f"(d[1]), "+f"(d[2]), "+f"(d[3]), "+f"(d[4]), "+f"(d[5]), "+f"(d[6]), "+f"(d[7]), "+f"(d[8]), "+f"(d[9]),
      "+f"(d[10]), "+f"(d[11]), "+f"(d[12]), "+f"(d[13]), "+f"(d[14]), "+f"(d[15]), "+f"(d[16]), "+f"(d[17]), "+f"(d[18]), "+f"(d[19]),
      "+f"(d[20]), "+f"(d[21]), "+f"(d[22]), "+f"(d[23])
    : "r"(a0), "r"(a1), "r"(a2), "r"(a3), "r"(db), "n"(HB));
}
template <uint32_t HB>
__device__ __forceinline__ void wgmma_rs_n48_tb1_z(float (&d)[24], uint32_t a0, uint32_t a1, uint32_t a2, uint32_t a3, uint32_t db) {
  asm volatile("{\n.reg .b64 db;\nmov.b64 db, {%28, %29};\n"
    "wgmma.mma_async.sync.aligned.m64n48k16.f32.bf16.bf16 "
    "{%0, %1, %2, %3, %4, %5, %6, %7, %8, %9, %10, %11, %12, %13, %14, %15, %16, %17, %18, %19, "
    "%20, %21, %22, %23}, "
    "{%24,%25,%26,%27}, db, 0, 1, 1, 1;\n}\n"
    : "=f"(d[0]), "=f"(d[1]), "=f"(d[2]), "=f"(d[3]), "=f"(d[4]), "=f"(d[5]), "=f"(d[6]), "=f"(d[7]), "=f"(d[8]), "=f"(d[9]),
      "=f"(d[10]), "=f"(d[11]), "=f"(d[12]), "=f"(d[13]), "=f"(d[14]), "=f"(d[15]), "=f"(d[16]), "=f"(d[17]), "=f"(d[18]), "=f"(d[19]),
      "=f"(d[20]), "=f"(d[21]), "=f"(d[22]), "=f"(d[23])
    : "r"(a0), "r"(a1), "r"(a2), "r"(a3), "r"(db), "n"(HB));
}
template <uint32_t HB>
__device__ __forceinline__ void wgmma_rs_n64_tb0_a(float (&d)[32], uint32_t a0, uint32_t a1, uint32_t a2, uint32_t a3, uint32_t db) {
  asm volatile("{\n.reg .b64 db;\nmov.b64 db, {%36, %37};\n"
    "wgmma.mma_async.sync.aligned.m64n64k16.f32.bf16.bf16 "
    "{%0, %1, %2, %3, %4, %5, %6, %7, %8, %9, %10, %11, %12, %13, %14, %15, %16, %17, %18, %19, "
    "%20, %21, %22, %23, %24, %25, %26, %27, %28, %29, %30, %31}, "
    "{%32,%33,%34,%35}, db, 1, 1, 1, 0;\n}\n"
    : "+f"(d[0]), "+f"(d[1]), "+f"(d[2]), "+f"(d[3]), "+f"(d[4]), "+f"(d[5]), "+f"(d[6]), "+f"(d[7]), "+f"(d[8]), "+f"(d[9]),
      "+f"(d[10]), "+f"(d[11]), "+f"(d[12]), "+f"(d[13]), "+f"(d[14]), "+f"(d[15]), "+f"(d[16]), "+f"(d[17]), "+f"(d[18]), "+f"(d[19]),
      "+f"(d[20]), "+f"(d[21]), "+f"(d[22]), "+f"(d[23]), "+f"(d[24]), "+f"(d[25]), "+f"(d[26]), "+f"(d[27]), "+f"(d[28]), "+f"(d[29]),
      "+f"(d[30]), "+f"(d[31])
    : "r"(a0), "r"(a1), "r"(a2), "r"(a3), "r"(db), "n"(HB));
}
template <uint32_t HB>
__device__ __forceinline__ void wgmma_rs_n64_tb0_z(float (&d)[32], uint32_t a0, uint32_t a1, uint32_t a2, uint32_t a3, uint32_t db) {
  asm volatile("{\n.reg .b64 db;\nmov.b64 db, {%36, %37};\n"
    "wgmma.mma_async.sync.aligned.m64n64k16.f32.bf16.bf16 "
    "{%0, %1, %2, %3, %4, %5, %6, %7, %8, %9, %10, %11, %12, %13, %14, %15, %16, %17, %18, %19, "
    "%20, %21, %22, %23, %24, %25, %26, %27, %28, %29, %30, %31}, "
    "{%32,%33,%34,%35}, db, 0, 1, 1, 0;\n}\n"
    : "=f"(d[0]), "=f"(d[1]), "=f"(d[2]), "=f"(d[3]), "=f"(d[4]), "=f"(d[5]), "=f"(d[6]), "=f"(d[7]), "=f"(d[8]), "=f"(d[9]),
      "=f"(d[10]), "=f"(d[11]), "=f"(d[12]), "=f"(d[13]), "=f"(d[14]), "=f"(d[15]), "=f"(d[16]), "=f"(d[17]), "=f"(d[18]), "=f"(d[19]),
      "=f"(d[20]), "=f"(d[21]), "=f"(d[22]), "=f"(d[23]), "=f"(d[24]), "=f"(d[25]), "=f"(d[26]), "=f"(d[27]), "=f"(d[28]), "=f"(d[29]),
      "=f"(d[30]), "=f"(d[31])
    : "r"(a0), "r"(a1), "r"(a2), "r"(a3), "r"(db), "n"(HB));
}
template <uint32_t HB>
__device__ __forceinline__ void wgmma_rs_n64_tb1_a(float (&d)[32], uint32_t a0, uint32_t a1, uint32_t a2, uint32_t a3, uint32_t db) {
  asm volatile("{\n.reg .b64 db;\nmov.b64 db, {%36, %37};\n"
    "wgmma.mma_async.sync.aligned.m64n64k16.f32.bf16.bf16 "
    "{%0, %1, %2, %3, %4, %5, %6, %7, %8, %9, %10, %11, %12, %13, %14, %15, %16, %17, %18, %19, "
    "%20, %21, %22, %23, %24, %25, %26, %27, %28, %29, %30, %31}, "
    "{%32,%33,%34,%35}, db, 1, 1, 1, 1;\n}\n"
    : "+f"(d[0]), "+f"(d[1]), "+f"(d[2]), "+f"(d[3]), "+f"(d[4]), "+f"(d[5]), "+f"(d[6]), "+f"(d[7]), "+f"(d[8]), "+f"(d[9]),
      "+f"(d[10]), "+f"(d[11]), "+f"(d[12]), "+f"(d[13]), "+f"(d[14]), "+f"(d[15]), "+f"(d[16]), "+f"(d[17]), "+f"(d[18]), "+f"(d[19]),
      "+f"(d[20]), "+f"(d[21]), "+f"(d[22]), "+f"(d[23]), "+f"(d[24]), "+f"(d[25]), "+f"(d[26]), "+f"(d[27]), "+f"(d[28]), "+f"(d[29]),
      "+f"(d[30]), "+f"(d[31])
    : "r"(a0), "r"(a1), "r"(a2), "r"(a3), "r"(db), "n"(HB));
}
template <uint32_t HB>
__device__ __forceinline__ void wgmma_rs_n64_tb1_z(float (&d)[32], uint32_t a0, uint32_t a1, uint32_t a2, uint32_t a3, uint32_t db) {
  asm volatile("{\n.reg .b64 db;\nmov.b64 db, {%36, %37};\n"
    "wgmma.mma_async.sync.aligned.m64n64k16.f32.bf16.bf16 "
    "{%0, %1, %2, %3, %4, %5, %6, %7, %8, %9, %10, %11, %12, %13, %14, %15, %16, %17, %18, %19, "
    "%20, %21, %22, %23, %24, %25, %26, %27, %28, %29, %30, %31}, "
    "{%32,%33,%34,%35}, db, 0, 1, 1, 1;\n}\n"
    : "=f"(d[0]), "=f"(d[1]), "=f"(d[2]), "=f"(d[3]), "=f"(d[4]), "=f"(d[5]), "=f"(d[6]), "=f"(d[7]), "=f"(d[8]), "=f"(d[9]),
      "=f"(d[10]), "=f"(d[11]), "=f"(d[12]), "=f"(d[13]), "=f"(d[14]), "=f"(d[15]), "=f"(d[16]), "=f"(d[17]), "=f"(d[18]), "=f"(d[19]),
      "=f"(d[20]), "=f"(d[21]), "=f"(d[22]), "=f"(d[23]), "=f"(d[24]), "=f"(d[25]), "=f"(d[26]), "=f"(d[27]), "=f"(d[28]), "=f"(d[29]),
      "=f"(d[30]), "=f"(d[31])
    : "r"(a0), "r"(a1), "r"(a2), "r"(a3), "r"(db), "n"(HB));
}
template <uint32_t HA, uint32_t HB>
__device__ __forceinline__ void wgmma_ss_n120_tb1_a(float (&d)[60], uint32_t da, uint32_t db) {
  asm volatile("{\n.reg .b64 da, db;\nmov.b64 da, {%60, %62};\nmov.b64 db, {%61, %63};\n"
    "wgmma.mma_async.sync.aligned.m64n120k16.f32.bf16.bf16 "
    "{%0, %1, %2, %3, %4, %5, %6, %7, %8, %9, %10, %11, %12, %13, %14, %15, %16, %17, %18, %19, "
    "%20, %21, %22, %23, %24, %25, %26, %27, %28, %29, %30, %31, %32, %33, %34, %35, %36, %37, %38, %39, "
    "%40, %41, %42, %43, %44, %45, %46, %47, %48, %49, %50, %51, %52, %53, %54, %55, %56, %57, %58, %59}, "
    "da, db, 1, 1, 1, 0, 1;\n}\n"
    : "+f"(d[0]), "+f"(d[1]), "+f"(d[2]), "+f"(d[3]), "+f"(d[4]), "+f"(d[5]), "+f"(d[6]), "+f"(d[7]), "+f"(d[8]), "+f"(d[9]),
      "+f"(d[10]), "+f"(d[11]), "+f"(d[12]), "+f"(d[13]), "+f"(d[14]), "+f"(d[15]), "+f"(d[16]), "+f"(d[17]), "+f"(d[18]), "+f"(d[19]),
      "+f"(d[20]), "+f"(d[21]), "+f"(d[22]), "+f"(d[23]), "+f"(d[24]), "+f"(d[25]), "+f"(d[26]), "+f"(d[27]), "+f"(d[28]), "+f"(d[29]),
      "+f"(d[30]), "+f"(d[31]), "+f"(d[32]), "+f"(d[33]), "+f"(d[34]), "+f"(d[35]), "+f"(d[36]), "+f"(d[37]), "+f"(d[38]), "+f"(d[39]),
      "+f"(d[40]), "+f"(d[41]), "+f"(d[42]), "+f"(d[43]), "+f"(d[44]), "+f"(d[45]), "+f"(d[46]), "+f"(d[47]), "+f"(d[48]), "+f"(d[49]),
      "+f"(d[50]), "+f"(d[51]), "+f"(d[52]), "+f"(d[53]), "+f"(d[54]), "+f"(d[55]), "+f"(d[56]), "+f"(d[57]), "+f"(d[58]), "+f"(d[59])
    : "r"(da), "r"(db), "n"(HA), "n"(HB));
}
template <uint32_t HA, uint32_t HB>
__device__ __forceinline__ void wgmma_ss_n80_tb1_a(float (&d)[40], uint32_t da, uint32_t db) {
  asm volatile("{\n.reg .b64 da, db;\nmov.b64 da, {%40, %42};\nmov.b64 db, {%41, %43};\n"
    "wgmma.mma_async.sync.aligned.m64n80k16.f32.bf16.bf16 "
    "{%0, %1, %2, %3, %4, %5, %6, %7, %8, %9, %10, %11, %12, %13, %14, %15, %16, %17, %18, %19, "
    "%20, %21, %22, %23, %24, %25, %26, %27, %28, %29, %30, %31, %32, %33, %34, %35, %36, %37, %38, %39}, "
    "da, db, 1, 1, 1, 0, 1;\n}\n"
    : "+f"(d[0]), "+f"(d[1]), "+f"(d[2]), "+f"(d[3]), "+f"(d[4]), "+f"(d[5]), "+f"(d[6]), "+f"(d[7]), "+f"(d[8]), "+f"(d[9]),
      "+f"(d[10]), "+f"(d[11]), "+f"(d[12]), "+f"(d[13]), "+f"(d[14]), "+f"(d[15]), "+f"(d[16]), "+f"(d[17]), "+f"(d[18]), "+f"(d[19]),
      "+f"(d[20]), "+f"(d[21]), "+f"(d[22]), "+f"(d[23]), "+f"(d[24]), "+f"(d[25]), "+f"(d[26]), "+f"(d[27]), "+f"(d[28]), "+f"(d[29]),
      "+f"(d[30]), "+f"(d[31]), "+f"(d[32]), "+f"(d[33]), "+f"(d[34]), "+f"(d[35]), "+f"(d[36]), "+f"(d[37]), "+f"(d[38]), "+f"(d[39])
    : "r"(da), "r"(db), "n"(HA), "n"(HB));
}


constexpr int HEADB = 98304;
constexpr uint32_t POLY = 0xDA;
constexpr int KB = 1024;
constexpr int NRAW = 16;
constexpr int SMEM_BYTES = 227 * KB;

__device__ __align__(1024) uint8_t g_img[96 * HEADB];
__device__ __align__(1024) uint8_t g_O[32 * 81920];
__device__ __align__(1024) uint4 g_H[32 * 8 * 672];
__device__ __align__(1024) uint4 g_P[256 * 8 * 4 * 160];
__device__ __align__(1024) uint8_t g_W2[64 * 30720];
__device__ __align__(128) uint4 g_st1[2048];
__device__ __align__(128) uint2 g_csq[2 * 1920];
__device__ __align__(128) uint2 g_cs1[1536];
__device__ __align__(128) float g_nrm[96 * 128];
constexpr int C_EPOCH = 0, C_W = 64, C_Q0 = C_W + 8 * 32, C_QA = C_Q0 + 96 * 8, C_O = C_QA + 96 * 8, C_H = C_O + 32 * 32, C_P = C_H + 32 * 32,
              C_END = C_P + 256 * 32;
__device__ __align__(128) uint32_t g_cnt[C_END];

constexpr int SBASE = 1024;
constexpr int SM_STG = 120 * KB;
constexpr int SM_CST = 192 * KB;
constexpr int SM_Q = 192 * KB;
constexpr int SM_O = 100 * KB;
constexpr int SM_O4 = 192 * KB;
constexpr int SM_RT = 216 * KB;
constexpr int SM_MISC = 221 * KB;
constexpr int SM_BAR = SM_MISC;
constexpr int SM_CSQ = SM_MISC + 1024;
constexpr int SM_ST1 = SM_CSQ + 1024;
constexpr int SM_B1 = SM_ST1 + 1024;
constexpr int SM_B2 = SM_B1 + 1536;
constexpr int SM_UNS = SM_B2 + 384;
constexpr int SM_EP = SM_UNS + 32;
constexpr int SM_K4 = SM_EP + 16;
constexpr int SM_OST = SM_EP + 32;
constexpr int B_F1 = 0, B_RAW1 = 10, B_AUX1 = 11, B_RAW2 = 12, B_KV = 13, B_UNS = 21, B_WO = 22, B_F3 = 23, B_FW = 33, B_RT = 49, B_CST = 52, B_KVX = 53, B_KVI = 56, B_SDONE = 57,
              B_C4 = 58, B_OREL1 = 58, B_DM0 = 60, B_SB = 61, B_GDONE = 77, B_XF = 79, B_ADONE = 81,
              B_C8 = 83, B_STG1 = 83,
              B_KVP = 86,
              B_C32 = 87, B_D1 = 87,
              B_KVF = 97, B_OREL0 = 101, B_DM = 102, B_DW = 105, B_END = 114;

__device__ __forceinline__ void wfence() { asm volatile("wgmma.fence.sync.aligned;" ::: "memory"); }
__device__ __forceinline__ void wcommit() { asm volatile("wgmma.commit_group.sync.aligned;" ::: "memory"); }
template <int N> __device__ __forceinline__ void wwait() { asm volatile("wgmma.wait_group.sync.aligned %0;" ::"n"(N) : "memory"); }
__host__ __device__ constexpr uint32_t dlo(uint32_t off, uint32_t lbo) { return ((SBASE + off) >> 4) | ((lbo >> 4) << 16); }
constexpr uint32_t dhi(uint32_t sbo, uint32_t swz) { return (sbo >> 4) | (swz << 30); }
constexpr uint32_t H128 = dhi(128, 0), H384 = dhi(384, 0), HSW = dhi(1024, 1), H32 = dhi(256, 3);
__device__ __forceinline__ void mbar_init(uint32_t b, int c) { asm volatile("mbarrier.init.shared::cta.b64 [%0], %1;" ::"r"(b), "r"(c) : "memory"); }
__device__ __forceinline__ void mbar_expect(uint32_t b, int bytes) { asm volatile("mbarrier.arrive.expect_tx.shared::cta.b64 _, [%0], %1;" ::"r"(b), "r"(bytes) : "memory"); }
__device__ __forceinline__ void mbar_arrive(uint32_t b) { asm volatile("mbarrier.arrive.shared::cta.b64 _, [%0];" ::"r"(b) : "memory"); }
__device__ __forceinline__ void mbar_arrive2(uint32_t b) {
  asm volatile("{\n.reg .b32 r, c;\nmov.u32 c, %%cluster_ctarank;\nxor.b32 c, c, 1;\nmapa.shared::cluster.u32 r, %0, c;\n"
               "mbarrier.arrive.shared::cta.b64 _, [%0];\nmbarrier.arrive.shared::cluster.b64 _, [r];\n}" ::"r"(b) : "memory");
}
__device__ __forceinline__ void mbar_wait(uint32_t b) {
  asm volatile("{\n.reg .pred p;\n.reg .u32 c;\nmov.u32 c,0;\nL1:\nmbarrier.try_wait.parity.shared::cta.b64 p, [%0], 0;\n@p bra L2;\n"
               "add.u32 c,c,1;\nsetp.lt.u32 p,c,4000000;\n@p bra L1;\ntrap;\nL2:\n}" ::"r"(b) : "memory");
}
__device__ __forceinline__ bool mbar_test(uint32_t b) {
  uint32_t r;
  asm volatile("{\n.reg .pred p;\nmbarrier.test_wait.parity.shared::cta.b64 p, [%1], 0;\nselp.u32 %0, 1, 0, p;\n}" : "=r"(r) : "r"(b) : "memory");
  return r;
}
__device__ __forceinline__ void bulk_g2s(uint32_t dst, const void* src, int bytes, uint32_t bar) {
  asm volatile("cp.async.bulk.shared::cluster.global.mbarrier::complete_tx::bytes [%0], [%1], %2, [%3];" ::"r"(dst), "l"(src), "r"(bytes), "r"(bar) : "memory");
}
__device__ __forceinline__ void bulk_s2g(void* dst, uint32_t src, int bytes) {
  asm volatile("cp.async.bulk.global.shared::cta.bulk_group [%0], [%1], %2;" ::"l"(dst), "r"(src), "r"(bytes) : "memory");
}
__device__ __forceinline__ void bulk_commit() { asm volatile("cp.async.bulk.commit_group;" ::: "memory"); }
__device__ __forceinline__ void bulk_wait0() { asm volatile("cp.async.bulk.wait_group 0;" ::: "memory"); }
__device__ __forceinline__ void tma2d(uint32_t dst, const CUtensorMap* tm, int c0, int c1, uint32_t bar) {
  asm volatile("cp.async.bulk.tensor.2d.shared::cluster.global.mbarrier::complete_tx::bytes [%0], [%1, {%3, %4}], [%2];" ::"r"(dst), "l"(tm), "r"(bar), "r"(c0), "r"(c1) : "memory");
}
__device__ __forceinline__ void tma2d_mc(uint32_t dst, const CUtensorMap* tm, int c0, int c1, uint32_t bar) {
  asm volatile("cp.async.bulk.tensor.2d.shared::cluster.global.mbarrier::complete_tx::bytes.multicast::cluster [%0], [%1, {%3, %4}], [%2], %5;"
               ::"r"(dst), "l"(tm), "r"(bar), "r"(c0), "r"(c1), "h"((uint16_t)3) : "memory");
}
__device__ __forceinline__ void tma3d(uint32_t dst, const CUtensorMap* tm, int c1, int c2, uint32_t bar) {
  asm volatile("cp.async.bulk.tensor.3d.shared::cluster.global.mbarrier::complete_tx::bytes [%0], [%1, {%3, %4, %5}], [%2];"
               ::"r"(dst), "l"(tm), "r"(bar), "r"(0), "r"(c1), "r"(c2) : "memory");
}
__device__ __forceinline__ void bulk_g2s_mc(uint32_t dst, const void* src, int bytes, uint32_t bar) {
  asm volatile("cp.async.bulk.shared::cluster.global.mbarrier::complete_tx::bytes.multicast::cluster [%0], [%1], %2, [%3], %4;"
               ::"r"(dst), "l"(src), "r"(bytes), "r"(bar), "h"((uint16_t)3) : "memory");
}
__device__ __forceinline__ void prefetch_l2(const void* p, int bytes) { asm volatile("cp.async.bulk.prefetch.L2.global [%0], %1;" ::"l"(p), "r"(bytes) : "memory"); }
__device__ __forceinline__ void fence_init() { asm volatile("fence.mbarrier_init.release.cluster;" ::: "memory"); }
__device__ __forceinline__ void cluster_arrive() { asm volatile("barrier.cluster.arrive.relaxed.aligned;" ::: "memory"); }
__device__ __forceinline__ void cluster_wait() { asm volatile("barrier.cluster.wait.aligned;" ::: "memory"); }
__device__ __forceinline__ void fence_async_smem() { asm volatile("fence.proxy.async.shared::cta;" ::: "memory"); }
__device__ __forceinline__ void fence_async_all() { asm volatile("fence.proxy.async.global;" ::: "memory"); }
__device__ __forceinline__ void bar_arrive(int id, int n) { asm volatile("bar.arrive %0, %1;" ::"r"(id), "r"(n) : "memory"); }
__device__ __forceinline__ void bar_sync(int id, int n) { asm volatile("bar.sync %0, %1;" ::"r"(id), "r"(n) : "memory"); }
__device__ __forceinline__ void fence_pub() { asm volatile("fence.proxy.async;" ::: "memory"); }
__device__ __forceinline__ void red_add(uint32_t* p, uint32_t v) { asm volatile("red.relaxed.gpu.global.add.u32 [%0], %1;" ::"l"(p), "r"(v) : "memory"); }
__device__ __forceinline__ void red_flag(uint32_t* p) { fence_pub(); red_add(p, 1); }
__device__ __forceinline__ void st_flag(uint32_t* p, uint32_t v) { asm volatile("fence.proxy.async;\nst.relaxed.gpu.global.u32 [%0], %1;" ::"l"(p), "r"(v) : "memory"); }
__device__ __forceinline__ uint32_t ld_flag(const uint32_t* p) { uint32_t v; asm volatile("ld.relaxed.gpu.global.u32 %0, [%1];" : "=r"(v) : "l"(p) : "memory"); return v; }
__device__ __forceinline__ void poll_all(const uint32_t* p, uint32_t target, bool act) {
  for (int it = 0;; it++) {
    bool ok = true;
    if (act) ok = (int32_t)(ld_flag(p) - target) >= 0;
    if (__all_sync(~0u, ok)) break;
    if (it > 2000000) __trap();
  }
}
__device__ __forceinline__ void poll_bit(uint32_t& rdy, uint32_t bit, const uint32_t* p, uint32_t target) {
  asm volatile("{\n.reg .pred p;\n.reg .u32 v, c;\nmov.u32 c, 0;\nL1:\nand.b32 v, %0, %1;\nsetp.ne.u32 p, v, 0;\n@p bra.uni L2;\n"
               "ld.relaxed.gpu.global.u32 v, [%2];\nsub.u32 v, v, %3;\nsetp.ge.s32 p, v, 0;\nvote.sync.ballot.b32 %0, p, 0xffffffff;\n"
               "add.u32 c, c, 1;\nsetp.lt.u32 p, c, 2000000;\n@p bra.uni L1;\ntrap;\nL2:\n}" : "+r"(rdy) : "r"(bit), "l"(p), "r"(target) : "memory");
}
__device__ __forceinline__ float ex2(float x) { float y; asm("ex2.approx.ftz.f32 %0, %1;" : "=f"(y) : "f"(x)); return y; }
__device__ __forceinline__ float rcp(float x) { float y; asm("rcp.approx.ftz.f32 %0, %1;" : "=f"(y) : "f"(x)); return y; }
__device__ __forceinline__ uint32_t packbf(float lo, float hi) { uint32_t r; asm("cvt.rn.bf16x2.f32 %0, %1, %2;" : "=r"(r) : "f"(hi), "f"(lo)); return r; }
__device__ __forceinline__ float bflo(uint32_t v) { return __uint_as_float(v << 16); }
__device__ __forceinline__ float bfhi(uint32_t v) { return __uint_as_float(v & 0xFFFF0000u); }
__device__ __forceinline__ void sts32(uint32_t a, uint32_t v) { asm volatile("st.shared.b32 [%0], %1;" ::"r"(a), "r"(v) : "memory"); }
__device__ __forceinline__ void sts64(uint32_t a, uint32_t v0, uint32_t v1) { asm volatile("st.shared.v2.b32 [%0], {%1,%2};" ::"r"(a), "r"(v0), "r"(v1) : "memory"); }
__device__ __forceinline__ void sts128f(uint32_t a, float4 v) { asm volatile("st.shared.v4.f32 [%0], {%1,%2,%3,%4};" ::"r"(a), "f"(v.x), "f"(v.y), "f"(v.z), "f"(v.w) : "memory"); }
__device__ __forceinline__ uint32_t lds32(uint32_t a) { uint32_t v; asm volatile("ld.shared.b32 %0, [%1];" : "=r"(v) : "r"(a) : "memory"); return v; }
__device__ __forceinline__ float2 lds64f(uint32_t a) { float2 v; asm volatile("ld.shared.v2.f32 {%0,%1}, [%2];" : "=f"(v.x), "=f"(v.y) : "r"(a) : "memory"); return v; }
__device__ __forceinline__ uint4 lds128(uint32_t a) { uint4 v; asm volatile("ld.shared.v4.b32 {%0,%1,%2,%3}, [%4];" : "=r"(v.x), "=r"(v.y), "=r"(v.z), "=r"(v.w) : "r"(a) : "memory"); return v; }
__device__ __forceinline__ float4 lds128f(uint32_t a) { float4 v; asm volatile("ld.shared.v4.f32 {%0,%1,%2,%3}, [%4];" : "=f"(v.x), "=f"(v.y), "=f"(v.z), "=f"(v.w) : "r"(a) : "memory"); return v; }
__device__ __forceinline__ void stsm4(uint32_t a, uint32_t r0, uint32_t r1, uint32_t r2, uint32_t r3) {
  asm volatile("stmatrix.sync.aligned.m8n8.x4.shared.b16 [%0], {%1,%2,%3,%4};" ::"r"(a), "r"(r0), "r"(r1), "r"(r2), "r"(r3) : "memory");
}
__device__ __forceinline__ uint32_t relu2_pair(float lo, float hi) {
  uint32_t r;
  asm("{\n.reg .b32 t;\ncvt.rn.relu.bf16x2.f32 t, %1, %2;\nmul.rn.bf16x2 %0, t, t;\n}" : "=r"(r) : "f"(hi), "f"(lo));
  return r;
}
__device__ __forceinline__ float ldcg_f(const float* p) { float v; asm volatile("ld.global.cg.f32 %0, [%1];" : "=f"(v) : "l"(p) : "memory"); return v; }
__device__ __forceinline__ float2 ldcg_f2(const float2* p) { float2 v; asm volatile("ld.global.cg.v2.f32 {%0,%1}, [%2];" : "=f"(v.x), "=f"(v.y) : "l"(p) : "memory"); return v; }
__device__ __forceinline__ uint4 ldcg128(const uint4* p) { uint4 v; asm volatile("ld.global.cg.v4.u32 {%0,%1,%2,%3}, [%4];" : "=r"(v.x), "=r"(v.y), "=r"(v.z), "=r"(v.w) : "l"(p) : "memory"); return v; }
__device__ __forceinline__ void stg128(uint4* p, uint32_t a, uint32_t b, uint32_t c, uint32_t d) { asm volatile("st.global.v4.u32 [%0], {%1,%2,%3,%4};" ::"l"(p), "r"(a), "r"(b), "r"(c), "r"(d) : "memory"); }
__device__ __forceinline__ uint4 ldx128(const uint4* p) {
  uint4 v;
  asm volatile("{\n.reg .b64 a, b;\nld.relaxed.gpu.global.v2.b64 {a, b}, [%4];\nmov.b64 {%0,%1}, a;\nmov.b64 {%2,%3}, b;\n}" : "=r"(v.x), "=r"(v.y), "=r"(v.z), "=r"(v.w) : "l"(p) : "memory");
  return v;
}
__device__ __forceinline__ void stx64(void* p, uint32_t a, uint32_t b) {
  asm volatile("{\n.reg .b64 a;\nmov.b64 a, {%1,%2};\nst.relaxed.gpu.global.b64 [%0], a;\n}" ::"l"(p), "r"(a), "r"(b) : "memory");
}
__device__ __forceinline__ uint32_t ldnc32(const uint32_t* p) { uint32_t v; asm volatile("ld.global.nc.u32 %0, [%1];" : "=r"(v) : "l"(p) : "memory"); return v; }
__device__ __forceinline__ uint32_t clk() { uint32_t c; asm volatile("mov.u32 %0, %%clock;" : "=r"(c)); return c; }
__device__ __forceinline__ int tid_now() { int v; asm volatile("mov.u32 %0, %%tid.x;" : "=r"(v)); return v; }
__device__ __forceinline__ float qsum(float v) { v += __shfl_xor_sync(~0u, v, 1); v += __shfl_xor_sync(~0u, v, 2); return v; }
__device__ __forceinline__ float sq2(uint32_t v, float a) { float l = bflo(v), h = bfhi(v); return fmaf(h, h, fmaf(l, l, a)); }
template <int N> __device__ __forceinline__ void zero_acc(float (&a)[N]) {
#pragma unroll
  for (int i = 0; i < N; i++) { a[i] = 0.f; asm volatile("" : "+f"(a[i])::"memory"); }
}

template <int N> __device__ __forceinline__ void keep(float (&a)[N]) {
#pragma unroll
  for (int i = 0; i < N; i++) asm volatile("" : "+f"(a[i])::"memory");
}

__device__ __forceinline__ uint32_t exp2_pair(float t0, float t1, uint32_t half, uint32_t ulp) {
  uint32_t u, mh, e, r;
  asm("prmt.b32 %0, %1, %2, 0x6521;" : "=r"(u) : "r"(__float_as_uint(t0)), "r"(__float_as_uint(t1)));
  asm("lop3.b32 %0, %1, 0x007F007F, %2, 0xEA;" : "=r"(mh) : "r"(u), "r"(half));
  asm("lop3.b32 %0, %1, 0xFF80FF80, %2, 0xEA;" : "=r"(e) : "r"(u), "r"(ulp));
  asm("fma.rn.bf16x2 %0, %1, %2, %3;" : "=r"(r) : "r"(u), "r"(mh), "r"(e));
  return r;
}

struct Params {
  const __nv_bfloat16 *x, *wqkv, *wo, *w1, *b1, *w2, *b2;
  __nv_bfloat16* out;
};

__device__ __forceinline__ int half_gh(int j, int nh) { return (j + 8 * nh) * 6; }

struct Maps { CUtensorMap x, wqkv, wo, w1, w2, wcs; };

__device__ __forceinline__ void load_w_stage1(const Maps& tm, uint32_t sb, int kc, int j, int rank) {
  const uint32_t s = sb + (kc & 3) * 48 * KB + 16 * KB + rank * 16 * KB, f = sb + SM_BAR + 8 * (B_F1 + kc);
  tma2d_mc(s, &tm.wqkv, j * 120 + rank * 960, kc * 64, f);
  tma2d_mc(s + 8 * KB, &tm.wqkv, j * 120 + rank * 960 + 64, kc * 64, f);
}
__device__ __forceinline__ void load_x_stage1(const Maps& tm, uint32_t sb, int kc, int rb) {
  const uint32_t f = sb + SM_BAR + 8 * (B_F1 + kc);
  mbar_expect(f, 48 * KB);
  tma2d(sb + (kc & 3) * 48 * KB, &tm.x, kc * 64, rb * 128, f);
}

__device__ __forceinline__ void warp_weights(const Maps& tm, uint32_t sb, int rb, int j, int head, int quarter) {
  const int lane = threadIdx.x & 31, rank = rb & 1;
  const uint32_t bar = sb + SM_BAR;
  if (lane == 0) {
#pragma unroll 1
    for (int kc = 4; kc < 10; kc++) {
      mbar_wait(bar + 8 * (B_D1 + kc - 4));
      load_w_stage1(tm, sb, kc, j, rank);
      load_x_stage1(tm, sb, kc, rb);
    }
  }
  __syncwarp();
  mbar_wait(bar + 8 * B_AUX1);
  const uint32_t ep = lds32(sb + SM_EP);
  const uint8_t* img = g_img + (size_t)head * HEADB;
  poll_all(g_cnt + C_Q0 + (head + 32 * lane) * 8 + (lane == 0 ? quarter : (head & 3)), ep * 4, lane < 3);
  mbar_wait(bar + 8 * (B_D1 + 9));
  fence_async_all();
  if (lane == 0) {
    const uint8_t* kp = img + 32 * HEADB + (head & 3) * 12 * KB;
#pragma unroll 1
    for (int i = 0; i < 4; i++) {
      const uint32_t f = bar + 8 * (i ? B_KVX + i - 1 : B_KV);
      mbar_expect(f, i ? 6 * KB : 18 * KB);
      bulk_g2s(sb + i * 3 * KB, kp + i * 3 * KB, 3 * KB, f);
      if (i == 0) bulk_g2s(sb + SM_Q, img + quarter * 12 * KB, 12 * KB, f);
      bulk_g2s(sb + 12 * KB + i * 3 * KB, kp + 32 * HEADB + i * 3 * KB, 3 * KB, f);
    }
  }
  __syncwarp();
#pragma unroll 1
  for (int i = 1; i < 8; i++) {
    if (i == 1) poll_all(g_cnt + C_Q0 + (head + 32 + 32 * lane) * 8 + ((head + 1) & 3), ep * 4, lane < 2);
    if (i == 2 || i == 4) {
      if (i == 2 && lane == 0) mbar_arrive(bar + 8 * B_KVI);
      poll_all(g_cnt + C_QA + (head + 32 * lane) * 8 + (i >> 2), ep * 16, lane < 3);
    }
    fence_async_all();
    if (lane == 0) {
      if (i == 5) mbar_wait(bar + 8 * B_SDONE);
      const uint32_t f = bar + 8 * (B_KV + i);
      const uint8_t* kp = img + 32 * HEADB + (i >> 2) * 48 * KB + ((head + i) & 3) * 12 * KB;
      mbar_expect(f, i == 7 ? 36 * KB : 24 * KB);
      bulk_g2s(sb + i * 24 * KB, kp, 12 * KB, f);
      bulk_g2s(sb + i * 24 * KB + 12 * KB, kp + 32 * HEADB, 12 * KB, f);
      if (i == 7) bulk_g2s(sb + SM_Q + 12 * KB, img + 48 * KB + quarter * 12 * KB, 12 * KB, f);
    }
    __syncwarp();
  }
  {
    const uint4 kn = ldcg128((const uint4*)(g_nrm + (32 + head) * 128) + lane), vn = ldcg128((const uint4*)(g_nrm + (64 + head) * 128) + lane);
    const float qn = ldcg_f(g_nrm + head * 128 + quarter * 32 + lane);
    const float km = __uint_as_float(__reduce_max_sync(~0u, max(max(kn.x, kn.y), max(kn.z, kn.w))));
    const float vm = __uint_as_float(__reduce_max_sync(~0u, max(max(vn.x, vn.y), max(vn.z, vn.w))));
    const bool safe = (qn * km <= 4096.f) && (vm <= 1e24f);
    const uint32_t sm = __ballot_sync(~0u, safe);
    if (lane < 8) sts32(sb + SM_UNS + lane * 4, ((sm >> (4 * lane)) & 15) != 15);
    __syncwarp();
    if (lane == 0) mbar_arrive(bar + 8 * B_UNS);
  }
  poll_all(g_cnt + C_W + j * 32, ep * 16, lane == 0);
  if (lane == 0) {
    fence_async_all();
    mbar_wait(bar + 8 * B_KVF);
    mbar_expect(bar + 8 * B_WO, 100 * KB);
#pragma unroll 1
    for (int c = 0; c < 5; c++) tma3d(sb + c * 20 * KB, &tm.wo, c * 128, j * 5, bar + 8 * B_WO);
    int slot = 6;
#pragma unroll 1
    for (int i = 0; i < 16; i++) {
      if (i < 4) mbar_wait(bar + 8 * (i == 0 ? B_KVP : B_DM + i - 1));
      else if (i >= 7) mbar_wait(bar + 8 * (B_DW + i - 7));
      if (i >= 2) mbar_wait(bar + 8 * (B_FW + i - 2));
      const uint32_t f = bar + 8 * (B_FW + i), d = sb + slot * 30 * KB;
      mbar_expect(f, 30 * KB);
      if (i < 8) {
        tma2d_mc(d + rank * 10 * KB, &tm.w1, j * 192 + rank * 64, ((j + i) & 7) * 80, f);
        if ((i & 1) == rank) tma2d_mc(d + 20 * KB, &tm.w1, j * 192 + 128, ((j + i) & 7) * 80, f);
      } else {
        bulk_g2s_mc(d + rank * 15 * KB, g_W2 + (j * 8 + ((j + i - 7) & 7)) * 30 * KB + rank * 15 * KB, 15 * KB, f);
      }
      slot = slot == 6 ? 0 : slot + 1;
    }
  }
}

__device__ __forceinline__ bool early_head(int gh, int rb) { return gh < 32 || (((rb >> 2) - gh) & 3) == 0; }
__device__ __forceinline__ void qkv_release(uint32_t sb, int rb, int j) {
  const int lane = threadIdx.x & 31;
  const uint32_t bar = sb + SM_BAR;
  const int gh = half_gh(j, lane >= 6) + (lane >= 6 ? lane - 6 : lane);
  const bool early = early_head(gh, rb);
  mbar_wait(bar + 8 * B_STG1);
  if (lane < 12 && early) red_flag(g_cnt + C_Q0 + gh * 8 + (rb >> 2));
  __syncwarp();
  const bool second = !early && (((rb >> 2) - gh) & 3) == 1;
  if (lane < 12 && second) {
    bulk_s2g(g_img + (size_t)gh * HEADB + rb * 3 * KB, sb + SM_STG + lane * 3 * KB, 3 * KB);
    bulk_commit();
    bulk_wait0();
    red_flag(g_cnt + C_Q0 + gh * 8 + (rb >> 2));
  }
  __syncwarp();
#pragma unroll 1
  for (int m = 0; m < 2; m++) {
    mbar_wait(bar + 8 * (B_STG1 + 1 + m));
    if (m) mbar_wait(bar + 8 * B_KVI);
    if (lane < 12) {
      if (m || !(early || second)) {
        bulk_s2g(g_img + (size_t)gh * HEADB + m * 48 * KB + rb * 3 * KB, sb + SM_STG + (m * 12 + lane) * 3 * KB, 3 * KB);
        bulk_commit();
        bulk_wait0();
      }
      red_flag(g_cnt + C_QA + gh * 8 + m);
    }
    __syncwarp();
  }
  if (lane == 0) mbar_arrive(bar + 8 * B_SDONE);
}

__device__ __forceinline__ void gather_tagged(uint4 (&v)[4], const uint4* a, const uint4* b, int o, uint32_t ep) {
  for (int it = 0;; it++) {
    v[0] = ldx128(a); v[1] = ldx128(a + o); v[2] = ldx128(b); v[3] = ldx128(b + o);
    bool ok = true;
#pragma unroll
    for (int i = 0; i < 4; i++) ok = ok && v[i].y == ep && v[i].w == ep;
    if (__all_sync(~0u, ok)) break;
    if (it > 1000000) __trap();
  }
}
__device__ __forceinline__ void gather_colsum(uint32_t sb, int j, int nh, uint32_t ep) {
  const int lane = threadIdx.x & 31, e = min(lane + 32, 59);
  const uint4* src = (const uint4*)g_csq + j * 60 + nh * 480;
  uint4 v[4];
  gather_tagged(v, src + lane, src + e, 960, ep);
  const uint32_t d = sb + SM_CSQ + nh * 480;
  sts64(d + lane * 8, __float_as_uint(__uint_as_float(v[0].x) + __uint_as_float(v[1].x)), __float_as_uint(__uint_as_float(v[0].z) + __uint_as_float(v[1].z)));
  sts64(d + e * 8, __float_as_uint(__uint_as_float(v[2].x) + __uint_as_float(v[3].x)), __float_as_uint(__uint_as_float(v[2].z) + __uint_as_float(v[3].z)));
  __syncwarp();
}
__device__ __forceinline__ void strip_colsum(const Maps& tm, uint32_t sb, int rb, int j) {
  const int lane = threadIdx.x & 31, c = rb * 8 + j;
  const uint32_t bar = sb + SM_BAR;
  const uint32_t ep = ld_flag(g_cnt + C_EPOCH) + 1;
  if (c < 120) {
    if (lane == 0) {
      mbar_wait(bar + 8 * B_F1);
      mbar_expect(bar + 8 * B_CST, 20 * KB);
      tma2d(sb + SM_CST, &tm.wcs, (c >> 1) * 32, (c & 1) * 320, bar + 8 * B_CST);
      tma2d(sb + SM_CST + 10 * KB, &tm.wcs, (c >> 1) * 32, (c & 1) * 320 + 160, bar + 8 * B_CST);
    }
    __syncwarp();
    mbar_wait(bar + 8 * B_CST);
    float a[8] = {0.f, 0.f, 0.f, 0.f, 0.f, 0.f, 0.f, 0.f};
#pragma unroll 2
    for (int i = 0; i < 40; i++) {
      const uint4 v = lds128(sb + SM_CST + i * 512 + lane * 16);
      a[0] += bflo(v.x); a[1] += bfhi(v.x); a[2] += bflo(v.y); a[3] += bfhi(v.y);
      a[4] += bflo(v.z); a[5] += bfhi(v.z); a[6] += bflo(v.w); a[7] += bfhi(v.w);
    }
#pragma unroll
    for (int n = 4; n; n >>= 1) {
      const bool up = lane & (4 * n);
#pragma unroll
      for (int i = 0; i < n; i++) a[i] = (up ? a[i + n] : a[i]) + __shfl_xor_sync(~0u, up ? a[i] : a[i + n], 4 * n);
    }
    stx64(g_csq + (c & 1) * 1920 + (c >> 1) * 32 + (lane & 3) * 8 + (lane >> 2), __float_as_uint(a[0]), ep);
  }
  gather_colsum(sb, j, 1, ep);
  if (lane == 0) mbar_arrive(bar + 8 * B_RAW2);
}

__device__ __forceinline__ void warp_aux(const Maps& tm, const Params& p, uint32_t sb, int rb, int j) {
  const int lane = threadIdx.x & 31;
  const uint32_t bar = sb + SM_BAR;
  const uint32_t ep = ld_flag(g_cnt + C_EPOCH) + 1;
  if (lane == 0) { sts32(sb + SM_EP, ep); sts64(sb + SM_K4, 0x3F003F00u, 0x00010001u); sts64(sb + SM_K4 + 8, 0u, 0u); }
  bar_sync(1, 544);
  stx64((uint2*)(g_st1 + rb * 128 + j * 16) + lane, lds32(sb + SM_OST + lane * 4), ep);
  gather_colsum(sb, j, 0, ep);
  mbar_wait(bar + 8 * B_RAW1);
  mbar_wait(bar + 8 * B_RAW2);
  if (lane == 0) { mbar_arrive(bar + 8 * B_AUX1); }
#pragma unroll 1
  for (int i = lane; i < 192; i += 32) {
    sts32(sb + SM_B1 + (i >> 1) * 16 + 8 + (i & 1) * 4, __float_as_uint(__bfloat162float(p.b1[j * 192 + i])));
    if (i < 80) sts32(sb + SM_B2 + i * 4, __float_as_uint(__bfloat162float(p.b2[j * 80 + i])));
  }
  __syncwarp();
  mbar_wait(bar + 8 * (B_KV + 2));
  if (lane == 0) {
    prefetch_l2((const uint8_t*)p.wo + blockIdx.x * 6400, 6400);
    prefetch_l2((const uint8_t*)p.w1 + blockIdx.x * 15360, 15360);
#pragma unroll 1
    for (int i = 0; i < 3; i++) {
      mbar_expect(bar + 8 * (B_RT + i), 5 * KB);
      tma3d(sb + SM_RT, &tm.w2, j * 192 + (rb & 1) * 96 + i * 32, (rb >> 1) * 5, bar + 8 * (B_RT + i));
      mbar_wait(bar + 8 * (B_RT + i));
      bulk_s2g(g_W2 + (j * 8 + (rb >> 1)) * 30 * KB + ((rb & 1) * 3 + i) * 5 * KB, sb + SM_RT, 5 * KB);
      bulk_commit();
      bulk_wait0();
    }
    red_flag(g_cnt + C_W + j * 32);
  }
  __syncwarp();
}

__device__ __forceinline__ void warp_release(uint32_t sb, int m, int rb, int j, int quarter) {
  const uint32_t bar = sb + SM_BAR;
  if ((threadIdx.x & 31) == 0) {
    const uint32_t ep = lds32(sb + SM_EP);
    ld_flag(g_cnt + C_H + (rb * 2 + m) * 32);
    ld_flag(g_cnt + C_P + ((rb * 8 + j) * 2 + m) * 32);
    mbar_wait(bar + 8 * (B_OREL1 + m));
    red_flag(g_cnt + C_O + ((quarter * 4 + m) * 2 + 1) * 32);
    mbar_wait(bar + 8 * (B_SB + m * 8));
    st_flag(g_cnt + C_H + (rb * 2 + m) * 32 + j, ep);
#pragma unroll 1
    for (int s = 1; s < 7;) {
      mbar_wait(bar + 8 * (B_SB + m * 8 + s));
      int e = s + 1;
      while (e < 7 && mbar_test(bar + 8 * (B_SB + m * 8 + e))) e++;
      fence_pub();
      for (; s < e; s++) red_add(g_cnt + C_P + ((rb * 8 + ((j + s) & 7)) * 2 + m) * 32 + j, 4);
    }
  }
}

__device__ __forceinline__ void warp_o(const Params& p, uint32_t sb, int rb, int j) {
  const int lane = threadIdx.x & 31;
  const uint32_t bar = sb + SM_BAR;
  const uint32_t ep = ld_flag(g_cnt + C_EPOCH) + 1;
  {
    uint4 v[4];
    gather_tagged(v, g_st1 + rb * 128 + lane, g_st1 + rb * 128 + 64 + lane, 32, ep);
#pragma unroll
    for (int i = 0; i < 4; i++) sts64(sb + SM_ST1 + (lane + 32 * i) * 8, v[i].x, v[i].z);
    __syncwarp();
  }
  if (lane == 0) mbar_arrive(bar + 8 * B_RAW1);
  mbar_wait(bar + 8 * (B_KV + 3));
  if (rb < 12) {
    const uint4* wp = (const uint4*)(p.w1 + (lane >> 1) * 1536 + (rb * 8 + j) * 16) + (lane & 1);
    float a[8] = {0.f, 0.f, 0.f, 0.f, 0.f, 0.f, 0.f, 0.f};
#pragma unroll 1
    for (int i = 0; i < 20; i++, wp += 32 * 192) {
      const uint4 v = __ldg(wp), u = __ldg(wp + 16 * 192);
      a[0] += bflo(v.x) + bflo(u.x); a[1] += bfhi(v.x) + bfhi(u.x); a[2] += bflo(v.y) + bflo(u.y); a[3] += bfhi(v.y) + bfhi(u.y);
      a[4] += bflo(v.z) + bflo(u.z); a[5] += bfhi(v.z) + bfhi(u.z); a[6] += bflo(v.w) + bflo(u.w); a[7] += bfhi(v.w) + bfhi(u.w);
    }
#pragma unroll
    for (int n = 4; n; n >>= 1) {
      const bool up = lane & (4 * n);
#pragma unroll
      for (int i = 0; i < n; i++) a[i] = (up ? a[i + n] : a[i]) + __shfl_xor_sync(~0u, up ? a[i] : a[i + n], 4 * n);
    }
    a[0] += __shfl_xor_sync(~0u, a[0], 2);
    if (!(lane & 2)) stx64(g_cs1 + (rb * 8 + j) * 16 + (lane & 1) * 8 + (lane >> 2), __float_as_uint(a[0]), ep);
  }
  {
    uint4 v[4];
    const uint4* src = (const uint4*)g_cs1 + j * 96 + lane;
    gather_tagged(v, src, src + 32, 32, ep);
    sts64(sb + SM_B1 + lane * 16, v[0].x, v[0].z);
    sts64(sb + SM_B1 + lane * 16 + 512, v[1].x, v[1].z);
    sts64(sb + SM_B1 + lane * 16 + 1024, v[3].x, v[3].z);
    __syncwarp();
  }
#pragma unroll 1
  for (int m = 0; m < 2; m++) {
    poll_all(g_cnt + C_O + (rb * 2 + m) * 32, ep * 32, lane == 0);
    if (lane == 0) {
      fence_async_all();
      if (m) { mbar_wait(bar + 8 * (B_KVF + 3)); mbar_wait(bar + 8 * B_DM0); }
#pragma unroll 1
      for (int i = 0; i < 5; i++) {
        const int c = m ? i : i == 0 ? 4 : i - 1;
        if (m == 0 && (i == 0 || i == 2 || i == 3)) mbar_wait(bar + 8 * (B_KVF + (i ? i - 1 : 0)));
        const uint32_t f = bar + 8 * (B_F3 + m * 5 + c);
        mbar_expect(f, 16 * KB);
        bulk_g2s(sb + (m == 0 && c == 4 ? SM_O4 : SM_O + c * 16 * KB), g_O + (rb * 2 + m) * 81920 + c * 16 * KB, 16 * KB, f);
      }
    }
    __syncwarp();
  }
  if (blockIdx.x == 0 && lane == 0) g_cnt[C_EPOCH] = ep;
}

__device__ __forceinline__ void qk_tile(float (&s)[32], const uint32_t (&q)[8], uint32_t a) {
  wgmma_rs_n64_tb0_z<H384>(s, q[0], q[1], q[2], q[3], a + (8 << 16));
  wgmma_rs_n64_tb0_a<H384>(s, q[4], q[5], q[6], q[7], a + 16);
}
__device__ __forceinline__ void pv_tile(float (&o)[12], const uint32_t (&pp)[16], uint32_t a) {
#pragma unroll
  for (int k = 0; k < 4; k++) wgmma_rs_n24_tb1_a<H128>(o, pp[4 * k], pp[4 * k + 1], pp[4 * k + 2], pp[4 * k + 3], a + 768 + k * 48 + (24 << 16));
}

__device__ __forceinline__ void attn_safe(float (&o_out)[12], uint32_t qa, uint32_t sb, int r, bool pad) {
  const uint32_t bar = sb + SM_BAR;
  const int lane = threadIdx.x & 31;
  uint32_t q[8];
  q[0] = lds32(qa); q[1] = lds32(qa + 384); q[2] = lds32(qa + 128); q[3] = lds32(qa + 512); q[4] = lds32(qa + 256); q[5] = lds32(qa + 640);
  q[6] = q[7] = 0;
  if (pad) q[4] = q[5] = 0;
  float s[32], o[12];
  zero_acc(o);
  float m0 = -INFINITY, m1 = -INFINITY;
#pragma unroll 1
  for (int jj = 0; jj < 32; jj++) {
    const uint32_t off = dlo(0, 0) + (jj >> 2) * 1536 + (jj & 3) * 192;
    mbar_wait(bar + 8 * (B_KV + (jj >> 2)));
    if (r == 1 && jj >= 20 && (jj & 3) == 0 && lane == 0) mbar_arrive(bar + 8 * (B_KVF + (jj >> 2) - 5));
#pragma unroll
    for (int i = 0; i < 8; i++) asm volatile("" : "+r"(q[i])::"memory");
    wfence();
    qk_tile(s, q, off);
    wcommit();
    wwait<0>();
    float a0 = m0, a1 = m1;
#pragma unroll
    for (int i = 0; i < 8; i++) { a0 = fmaxf(a0, fmaxf(s[4 * i], s[4 * i + 1])); a1 = fmaxf(a1, fmaxf(s[4 * i + 2], s[4 * i + 3])); }
    a0 = fmaxf(a0, __shfl_xor_sync(~0u, a0, 1)); a0 = fmaxf(a0, __shfl_xor_sync(~0u, a0, 2));
    a1 = fmaxf(a1, __shfl_xor_sync(~0u, a1, 1)); a1 = fmaxf(a1, __shfl_xor_sync(~0u, a1, 2));
    const float c0 = ex2(m0 - a0), c1 = ex2(m1 - a1);
    m0 = a0; m1 = a1;
    uint32_t pp[16];
#pragma unroll
    for (int i = 0; i < 8; i++) {
      const uint32_t sg = ((POLY >> i) & 1) ? 0x80008000u : 0u;
      pp[2 * i] = packbf(ex2(s[4 * i] - m0), ex2(s[4 * i + 1] - m0)) ^ sg;
      pp[2 * i + 1] = packbf(ex2(s[4 * i + 2] - m1), ex2(s[4 * i + 3] - m1)) ^ sg;
    }
#pragma unroll
    for (int i = 0; i < 3; i++) { o[4 * i] *= c0; o[4 * i + 1] *= c0; o[4 * i + 2] *= c1; o[4 * i + 3] *= c1; }
#pragma unroll
    for (int i = 0; i < 12; i++) asm volatile("" : "+f"(o[i])::"memory");
    wfence();
    pv_tile(o, pp, off);
    wcommit();
    wwait<0>();
  }
#pragma unroll
  for (int i = 0; i < 12; i++) asm volatile("mov.b32 %0, %1;" : "=f"(o_out[i]) : "f"(o[i]) : "memory");
}

__device__ __forceinline__ void add_frag(float (&s)[40], const uint4 (&v)[5]) {
#pragma unroll
  for (int k = 0; k < 5; k++) {
    s[8 * k] += bflo(v[k].x); s[8 * k + 1] += bfhi(v[k].x); s[8 * k + 2] += bflo(v[k].y); s[8 * k + 3] += bfhi(v[k].y);
    s[8 * k + 4] += bflo(v[k].z); s[8 * k + 5] += bfhi(v[k].z); s[8 * k + 6] += bflo(v[k].w); s[8 * k + 7] += bfhi(v[k].w);
  }
}
__device__ __forceinline__ void ffn2_x(float (&x)[24], const uint32_t (&ga)[48], uint32_t b) {
  wgmma_rs_n48_tb1_z<H32>(x, ga[0], ga[1], ga[2], ga[3], b);
#pragma unroll
  for (int k = 1; k < 12; k++) wgmma_rs_n48_tb1_a<H32>(x, ga[4 * k], ga[4 * k + 1], ga[4 * k + 2], ga[4 * k + 3], b + (k / 2) * 320 + (k % 2) * 32);
}
__device__ __forceinline__ void ffn2_y(float (&y)[16], const uint32_t (&ga)[48], uint32_t b) {
  wgmma_rs_n32_tb1_z<H32>(y, ga[0], ga[1], ga[2], ga[3], b + 192);
#pragma unroll
  for (int k = 1; k < 12; k++) wgmma_rs_n32_tb1_a<H32>(y, ga[4 * k], ga[4 * k + 1], ga[4 * k + 2], ga[4 * k + 3], b + 192 + (k / 2) * 320 + (k % 2) * 32);
}
template <int N> __device__ __forceinline__ void store_frag(uint4* d, const float (&a)[N]) {
#pragma unroll
  for (int k = 0; k < N / 8; k++)
    stg128(d + k * 32, packbf(a[8 * k], a[8 * k + 1]), packbf(a[8 * k + 2], a[8 * k + 3]), packbf(a[8 * k + 4], a[8 * k + 5]), packbf(a[8 * k + 6], a[8 * k + 7]));
}

__global__ void __cluster_dims__(2, 1, 1) __launch_bounds__(640, 1)
block_kernel(const __grid_constant__ Maps tm, const Params p) {
  extern __shared__ __align__(1024) uint8_t smem[];
  const uint32_t sb = (uint32_t)__cvta_generic_to_shared(smem);
  const uint32_t bar = sb + SM_BAR;
  const int rank = blockIdx.x & 1, cl = blockIdx.x >> 1, tp = cl - 4;
  const int grp = cl < 4 ? 0 : tp < 32 ? (tp & 7) : 1 + (tp - 32) % 7;
  const int j = cl < 4 ? 4 + cl : tp < 32 ? (tp >> 3) : 4 + (tp - 32) / 7;
  const int rb = grp * 2 + rank;
  const int head = grp * 4 + (j >> 1), quarter = (j & 1) * 2 + rank;
  const int warp = __reduce_max_sync(~0u, threadIdx.x >> 5), lane = threadIdx.x & 31;

  if (warp >= 16) {
    asm volatile("setmaxnreg.dec.sync.aligned.u32 32;");
    const int st = warp - 16;
    if (lane == 0) {
      mbar_init(bar + 8 * (B_F1 + st), 1);
      if (st) { mbar_init(bar + 8 * (B_D1 + st - 1), 32); mbar_init(bar + 8 * (B_D1 + st + 2), 32); }
      fence_init();
    }
    __syncwarp();
    cluster_arrive();
    if (st == 0 && lane == 0) load_x_stage1(tm, sb, 0, rb);
    __syncwarp();
    cluster_wait();
    bar_arrive(6, 640);
    if (st < 2 && lane == 0) {
      if (st) { const uint32_t t0 = clk(); while (clk() - t0 < 600u * st) {} }
      load_w_stage1(tm, sb, st, j, rank);
      if (st) load_x_stage1(tm, sb, st, rb);
    }
    __syncwarp();
    bar_sync(0, 640);
    if (st >= 2 && lane == 0) {
      mbar_wait(bar + 8 * (B_F1 + st - 2));
      load_w_stage1(tm, sb, st, j, rank);
      load_x_stage1(tm, sb, st, rb);
    }
    __syncwarp();
    if (warp == 16) {
      if ((sb & 0xFFFFFF) != SBASE) __trap();
      warp_weights(tm, sb, rb, j, head, quarter);
    } else {
      if (warp == 17) {
        strip_colsum(tm, sb, rb, j);
        qkv_release(sb, rb, j);
        mbar_wait(bar + 8 * B_OREL0);
        if (lane < 4) red_flag(g_cnt + C_O + (quarter * 4 + lane) * 64);
        __syncwarp();
      }
      if (warp == 18) warp_aux(tm, p, sb, rb, j);
      if (warp < 19) warp_release(sb, warp - 17, rb, j, quarter);
      else warp_o(p, sb, rb, j);
    }
    return;
  }

  cluster_arrive();
  const int wg = warp >> 2, w = warp & 3, g = lane >> 2, t = lane & 3;
  const int mh = wg & 1, nh = wg >> 1;
  {
    asm volatile("setmaxnreg.inc.sync.aligned.u32 112;");
    if (lane == 0) {
#pragma unroll 1
      for (int i = 4 + warp; i < B_END - 6; i += 16) mbar_init(bar + 8 * (i < B_C32 ? i : i + 6), i < B_C4 ? 1 : i < B_C8 ? 4 : i < B_KVP ? 8 : i < B_C32 ? 40 : 16);
      fence_init();
    }
    __syncwarp();
    bar_arrive(0, 640);
    bar_sync(6, 640);
    uint2 xr[5];
    const uint2* xp = (const uint2*)(p.x + (size_t)(rb * 128 + j * 16 + warp) * 640);
#pragma unroll
    for (int i = 0; i < 5; i++) xr[i] = __ldg(xp + i * 32 + lane);

    float acc[60], mean = 0.f;
    zero_acc(acc);
    const uint32_t dA = dlo(0, 16) + mh * 512, dB = dlo(16 * KB, 8 * KB) + nh * 1024;
#pragma unroll 1
    for (int kc = 0; kc < 10; kc++) {
      const int so = (kc & 3) * (48 * KB / 16);
      mbar_wait(bar + 8 * (B_F1 + kc));
      wfence();
#pragma unroll
      for (int k = 0; k < 4; k++) wgmma_ss_n120_tb1_a<HSW, HSW>(acc, dA + so + k * 2, dB + so + k * 128);
      wcommit();
      if (kc) {
        wwait<1>();
        if (lane == 0) { if (kc < 7) mbar_arrive2(bar + 8 * (B_D1 + kc - 1)); else mbar_arrive(bar + 8 * (B_D1 + kc - 1)); }
      }
      if (kc == 1) {
#pragma unroll
        for (int i = 0; i < 5; i++) asm volatile("" : "+r"(xr[i].x), "+r"(xr[i].y)::"memory");
        float s = 0.f;
#pragma unroll
        for (int i = 0; i < 5; i++) s += (bflo(xr[i].x) + bfhi(xr[i].x)) + (bflo(xr[i].y) + bfhi(xr[i].y));
#pragma unroll
        for (int o = 16; o; o >>= 1) s += __shfl_xor_sync(~0u, s, o);
        mean = s * (1.f / 640.f);
      }
      if (kc == 1) {
        asm volatile("" : "+f"(mean)::"memory");
        float v = 0.f;
#pragma unroll
        for (int i = 0; i < 5; i++) {
          const float a = bflo(xr[i].x) - mean, b = bfhi(xr[i].x) - mean, c = bflo(xr[i].y) - mean, d = bfhi(xr[i].y) - mean;
          v += (a * a + b * b) + (c * c + d * d);
        }
#pragma unroll
        for (int o = 16; o; o >>= 1) v += __shfl_xor_sync(~0u, v, o);
        if (lane == 0) sts64(sb + SM_OST + warp * 8, __float_as_uint(mean), __float_as_uint(rsqrtf(v * (1.f / 640.f) + 1e-5f)));
        bar_arrive(1, 544);
      }
    }
    wwait<0>();
    keep(acc);
    if (lane == 0) mbar_arrive(bar + 8 * (B_D1 + 9));
    mbar_wait(bar + 8 * (B_D1 + 7));
    mbar_wait(bar + 8 * (mh ? B_STG1 : B_AUX1));
    const float2 st0 = lds64f(sb + SM_ST1 + (mh * 64 + w * 16 + g) * 8), st1 = lds64f(sb + SM_ST1 + (mh * 64 + w * 16 + g + 8) * 8);
    const int gh0 = half_gh(j, nh);
    const bool py0 = (POLY >> (2 * w)) & 1, py1 = (POLY >> (2 * w + 1)) & 1;
    const uint32_t stg = sb + SM_STG + (mh * 12 + nh * 6) * 3 * KB + 2 * w * 384;
    const uint32_t rowa = stg + g * 16 + t * 4 + 256;
    const uint32_t stm = stg + ((lane >> 3) & 1) * 384 + (lane >> 4) * 128 + (lane & 7) * 16;
    uint32_t v[3][10];
#pragma unroll
    for (int pr = 0; pr < 3; pr++) {
      const int type = (gh0 + pr * 2) >> 5;
      float m0 = st0.y, m1 = st1.y;
      if (type == 0) { m0 *= 0.32259784f; m1 *= 0.32259784f; }
      if (type == 2) { if (py0) m0 = -m0; if (py1) m1 = -m1; }
      uint32_t(&a)[10] = v[pr];
#pragma unroll
      for (int r = 0; r < 5; r++) {
        const int nb = pr * 5 + r;
        const float2 c = lds64f(sb + SM_CSQ + (nh * 120 + nb * 8 + t * 2) * 4);
        a[2 * r] = packbf(fmaf(-st0.x, c.x, acc[4 * nb]) * m0, fmaf(-st0.x, c.y, acc[4 * nb + 1]) * m0);
        a[2 * r + 1] = packbf(fmaf(-st1.x, c.x, acc[4 * nb + 2]) * m1, fmaf(-st1.x, c.y, acc[4 * nb + 3]) * m1);
      }
      const uint32_t pq = (t & 1) ? 0x0000BDB4u : 0x42FD4380u, pk = (t & 1) ? 0x00003F80u : 0x3F803F80u, pv = (t & 1) ? 0u : 0x00003F80u;
      const uint32_t p0 = type == 0 ? pq : type == 1 ? (py0 ? pk : 0u) : (py0 && pv ? 0x0000BF80u : pv);
      const uint32_t p1 = type == 0 ? pq : type == 1 ? (py1 ? pk : 0u) : (py1 && pv ? 0x0000BF80u : pv);
      stsm4(stm + pr * 6 * KB, a[0], a[1], a[2], a[3]);
      sts32(rowa + pr * 6 * KB, t < 2 ? a[4] : p0);
      sts32(rowa + pr * 6 * KB + 384, t < 2 ? a[5] : p1);
      stsm4(stm + pr * 6 * KB + 3 * KB, a[6], a[7], a[8], a[9]);
      sts32(rowa + pr * 6 * KB + 3 * KB, t < 2 ? p0 : a[4]);
      sts32(rowa + pr * 6 * KB + 3 * KB + 384, t < 2 ? p1 : a[5]);
    }
    fence_async_smem();
    __syncwarp();
    if (mh == 0) {
      uint4* const ip = (uint4*)(g_img + (size_t)gh0 * HEADB + rb * 3 * KB + 2 * w * 384) + lane;
#pragma unroll
      for (int hd = 0; hd < 6; hd++) {
        if (early_head(gh0 + hd, rb)) {
          const uint4 a = lds128(stg + hd * 3 * KB + lane * 16), b = lds128(stg + hd * 3 * KB + 512 + (lane & 15) * 16);
          stg128(ip + hd * (HEADB / 16), a.x, a.y, a.z, a.w);
          if (lane < 16) stg128(ip + hd * (HEADB / 16) + 32, b.x, b.y, b.z, b.w);
        }
      }
      __syncwarp();
      if (lane == 0) mbar_arrive(bar + 8 * B_STG1);
    }
    uint32_t nrm = 0;
#pragma unroll
    for (int pr = 0; pr < 3; pr++) {
      const uint32_t(&a)[10] = v[pr];
      const float c0 = sq2(a[4], 0.f), c1 = sq2(a[5], 0.f);
      const float e0 = sq2(a[0], sq2(a[2], t < 2 ? c0 : 0.f)), e1 = sq2(a[1], sq2(a[3], t < 2 ? c1 : 0.f));
      const float o0 = sq2(a[6], sq2(a[8], t < 2 ? 0.f : c0)), o1 = sq2(a[7], sq2(a[9], t < 2 ? 0.f : c1));
      const float x0 = (t & 2 ? o0 : e0) + __shfl_xor_sync(~0u, t & 2 ? e0 : o0, 2), x1 = (t & 2 ? o1 : e1) + __shfl_xor_sync(~0u, t & 2 ? e1 : o1, 2);
      const uint32_t n = __float_as_uint((t & 1 ? x1 : x0) + __shfl_xor_sync(~0u, t & 1 ? x0 : x1, 1));
      const uint32_t ne = __reduce_max_sync(~0u, t & 2 ? 0u : n), no = __reduce_max_sync(~0u, t & 2 ? n : 0u);
      if ((lane >> 1) == pr) nrm = lane & 1 ? no : ne;
    }
    if (lane < 6) g_nrm[(gh0 + lane) * 128 + rb * 8 + mh * 4 + w] = __uint_as_float(nrm);
    __syncwarp();
    if (lane == 0) mbar_arrive(bar + 8 * (B_STG1 + 1 + mh));
    cluster_wait();
  }
  {
    const int odd = head & 1;
    const bool pad = (t >> 1) != odd;
    mbar_wait(bar + 8 * B_KV);
#pragma unroll 1
    for (int r = 0; r < 2; r++) {
      const uint32_t qa = sb + SM_Q + r * 12 * KB + wg * 3 * KB + 2 * w * 384 + g * 16 + t * 4;
      float o[12];
      uint32_t unsafe = r == 1 ? __reduce_max_sync(~0u, lds32(sb + SM_UNS + (2 * wg + 1) * 4)) : 0u;
      if (!unsafe) {
        uint32_t q[8];
        q[0] = lds32(qa); q[1] = lds32(qa + 384); q[2] = lds32(qa + 128); q[3] = lds32(qa + 512); q[4] = lds32(qa + 256); q[5] = lds32(qa + 640);
        const uint4 k4 = lds128(sb + SM_K4);
        q[6] = k4.z; q[7] = k4.w;
        zero_acc(o);
#pragma unroll
        for (int i = 0; i < 8; i++) asm volatile("" : "+r"(q[i])::"memory");
        float s[32];
        uint32_t pb[2][16];
        wfence();
        qk_tile(s, q, dlo(0, 0));
        wcommit();
        wcommit();
#pragma unroll 1
        for (int sl = 0; sl < 8; sl++) {
          const uint32_t off0 = dlo(0, 0) + sl * 1536;
#pragma unroll
          for (int h = 0; h < 4; h++) {
            if (h == 3 && r == 0 && sl < 7) mbar_wait(bar + 8 * (B_KV + 1 + sl));
            if (h < 3 && r + sl == 0) mbar_wait(bar + 8 * (B_KVX + h));
            wwait<1>();
            uint32_t(&pp)[16] = pb[h & 1];
            if (h == 1 && r == 1 && sl >= 5 && lane == 0) mbar_arrive(bar + 8 * (B_KVF - 5 + sl));
#pragma unroll
            for (int i = 0; i < 8; i++) {
              if ((POLY >> i) & 1) {
                pp[2 * i] = exp2_pair(s[4 * i], s[4 * i + 1], k4.x, k4.y); pp[2 * i + 1] = exp2_pair(s[4 * i + 2], s[4 * i + 3], k4.x, k4.y);
              } else {
                pp[2 * i] = packbf(ex2(s[4 * i]), ex2(s[4 * i + 1])); pp[2 * i + 1] = packbf(ex2(s[4 * i + 2]), ex2(s[4 * i + 3]));
              }
            }
            wfence();
            qk_tile(s, q, h < 3 ? off0 + h * 192 + 192 : sl < 7 ? off0 + 1536 : off0);
            wcommit();
            pv_tile(o, pp, off0 + h * 192);
            wcommit();
          }
        }
        wwait<0>();
        keep(o);
      }
      if (r == 0) {
        mbar_wait(bar + 8 * B_UNS);
        unsafe = __reduce_max_sync(~0u, lds32(sb + SM_UNS + 2 * wg * 4));
      }
      if (unsafe) attn_safe(o, qa, sb, r, pad);
      if (r == 1) {
        if (lane == 0) { mbar_arrive(bar + 8 * (B_KVF + 3)); mbar_arrive2(bar + 8 * B_KVP); }
      }
      const int sl = (lane & ~3) | (2 - 2 * odd);
      const float i0 = rcp(__shfl_sync(~0u, o[8], sl)), i1 = rcp(__shfl_sync(~0u, o[10], sl));
      const int orh = (quarter * 4 + wg) * 2 + r;
      uint8_t* op = g_O + orh * 81920 + (head >> 1) * 5 * KB + (w * 16 + g) * 16 + t * 4;
      uint8_t* oa = op + odd * 3 * KB;
      *(uint32_t*)(oa) = packbf(o[0] * i0, o[1] * i0);
      *(uint32_t*)(oa + 128) = packbf(o[2] * i1, o[3] * i1);
      *(uint32_t*)(oa + KB) = packbf(o[4] * i0, o[5] * i0);
      *(uint32_t*)(oa + KB + 128) = packbf(o[6] * i1, o[7] * i1);
      if (!pad) {
        *(uint32_t*)(op + 2 * KB) = packbf(o[8] * i0, o[9] * i0);
        *(uint32_t*)(op + 2 * KB + 128) = packbf(o[10] * i1, o[11] * i1);
      }
      __syncwarp();
      if (r == 0 || nh == 0) {
        if (lane == 0) mbar_arrive(bar + 8 * (r == 0 ? B_OREL0 : B_OREL1 + mh));
      } else {
        bar_sync(2 + wg, 128);
        if ((threadIdx.x & 127) == 0) red_flag(g_cnt + C_O + orh * 32);
      }
    }
  }
  const int rh = rb * 2 + mh;
  if (nh == 1) {
    asm volatile("setmaxnreg.dec.sync.aligned.u32 24;");
    mbar_wait(bar + 8 * (B_GDONE + mh));
    asm volatile("setmaxnreg.inc.sync.aligned.u32 104;");
    const uint32_t ep = lds32(sb + SM_EP);
    float sum[40];
#pragma unroll
    for (int i = 0; i < 10; i++) {
      const float2 b = lds64f(sb + SM_B2 + (i * 8 + t * 2) * 4);
      sum[4 * i] = sum[4 * i + 2] = b.x; sum[4 * i + 1] = sum[4 * i + 3] = b.y;
    }
    uint4 v[5];
#pragma unroll
    for (int k = 0; k < 5; k++) v[k] = ldcg128(g_H + (rh * 8 + j) * 672 + w * 160 + k * 32 + lane);
    add_frag(sum, v);
    const int pb = (rb * 8 + j) * 2 + mh;
    uint32_t pending = 0xFF ^ (1u << j);
    const uint32_t* const fl = g_cnt + C_P + pb * 32 + (lane & 7);
    const uint4* const sp = g_P + (pb * 32 + w) * 160 + lane;
    uint32_t f = ld_flag(fl);
#pragma unroll 1
    for (int it = 0; pending; it++) {
      const uint32_t rdy = __ballot_sync(~0u, (int32_t)(f - 4 * ep) >= 0) & pending, rdy2 = rdy & (rdy - 1);
      uint4 u[5];
      if (rdy) {
#pragma unroll
        for (int k = 0; k < 5; k++) v[k] = ldcg128(sp + (__ffs(rdy) - 1) * 640 + k * 32);
      }
      if (rdy2) {
#pragma unroll
        for (int k = 0; k < 5; k++) u[k] = ldcg128(sp + (__ffs(rdy2) - 1) * 640 + k * 32);
      }
      f = ld_flag(fl);
      if (rdy) add_frag(sum, v);
      if (rdy2) add_frag(sum, u);
      pending ^= rdy ^ (rdy2 & (rdy2 - 1));
      if (it > 2000000) __trap();
    }
    mbar_wait(bar + 8 * (B_ADONE + mh));
    const uint32_t hand = sb + (30 + 30 * mh) * KB + (threadIdx.x & 127) * 16;
    const uint32_t ost = sb + (50 + 30 * mh) * KB + w * 2560;
#pragma unroll
    for (int k = 0; k < 5; k++) {
      const float4 a = lds128f(hand + k * 4 * KB), b = lds128f(hand + k * 4 * KB + 2 * KB);
      stsm4(ost + (lane & 15) * 160 + (lane >> 4) * 16 + k * 32, packbf(a.x + sum[8 * k], a.y + sum[8 * k + 1]), packbf(a.z + sum[8 * k + 2], a.w + sum[8 * k + 3]),
            packbf(b.x + sum[8 * k + 4], b.y + sum[8 * k + 5]), packbf(b.z + sum[8 * k + 6], b.w + sum[8 * k + 7]));
    }
    __syncwarp();
    uint4* op = (uint4*)(p.out + (size_t)(rh * 64 + w * 16) * 640 + j * 80);
#pragma unroll
    for (int k = 0; k < 5; k++) {
      const int e = k * 32 + lane;
      const uint4 v = lds128(ost + e * 16);
      stg128(op + (e / 10) * 80 + e % 10, v.x, v.y, v.z, v.w);
    }
    return;
  }
  uint32_t xr[20];
  {
    const uint32_t* xp = (const uint32_t*)(p.x + (size_t)(rh * 64 + w * 16 + g) * 640 + j * 80) + t;
    if (mh) {
      mbar_wait(bar + 8 * B_DM0);
#pragma unroll
      for (int i = 0; i < 10; i++) { xr[2 * i] = ldnc32(xp + i * 4); xr[2 * i + 1] = ldnc32(xp + i * 4 + 8 * 320); }
    }
    float acc[40];
    zero_acc(acc);
    const uint32_t o4 = mh ? 0 : (SM_O4 - SM_O - 64 * KB) / 16;
    mbar_wait(bar + 8 * B_WO);
#pragma unroll
    for (int c = 0; c < 5; c++) {
      mbar_wait(bar + 8 * (B_F3 + c) + mh * 40);
      wfence();
#pragma unroll
      for (int k = 0; k < 8; k++) wgmma_ss_n80_tb1_a<H128, H32>(acc, dlo(SM_O + c * 16 * KB + k * 2 * KB, KB) + (c == 4 ? o4 : 0), dlo(c * 20 * KB + k * 512, 4 * KB));
      wcommit();
      if (c == 2 && mh == 0) {
#pragma unroll
        for (int i = 0; i < 10; i++) { xr[2 * i] = ldnc32(xp + i * 4); xr[2 * i + 1] = ldnc32(xp + i * 4 + 8 * 320); }
      }
      if (c == 2 || c == 3) { wwait<1>(); if (lane == 0) mbar_arrive2(bar + 8 * (B_DM + c - 2)); }
    }
    wwait<0>();
    keep(acc);
    if (lane == 0) {
      mbar_arrive2(bar + 8 * (B_DM + 2));
      if (mh == 0) { mbar_arrive(bar + 8 * B_DM0); mbar_arrive2(bar + 8 * B_KVP); }
    }
    float s0 = 0.f, s1 = 0.f;
#pragma unroll
    for (int i = 0; i < 10; i++) {
      xr[2 * i] = packbf(acc[4 * i] + bflo(xr[2 * i]), acc[4 * i + 1] + bfhi(xr[2 * i]));
      xr[2 * i + 1] = packbf(acc[4 * i + 2] + bflo(xr[2 * i + 1]), acc[4 * i + 3] + bfhi(xr[2 * i + 1]));
      s0 += bflo(xr[2 * i]) + bfhi(xr[2 * i]); s1 += bflo(xr[2 * i + 1]) + bfhi(xr[2 * i + 1]);
    }
    uint4* hp = g_H + (rh * 8 + j) * 672;
#pragma unroll
    for (int k = 0; k < 5; k++) stg128(hp + w * 160 + k * 32 + lane, xr[4 * k], xr[4 * k + 1], xr[4 * k + 2], xr[4 * k + 3]);
    s0 = qsum(s0) * (1.f / 80.f); s1 = qsum(s1) * (1.f / 80.f);
    float v0 = 0.f, v1 = 0.f;
#pragma unroll
    for (int i = 0; i < 10; i++) {
      const float a = bflo(xr[2 * i]) - s0, b = bfhi(xr[2 * i]) - s0, c = bflo(xr[2 * i + 1]) - s1, d = bfhi(xr[2 * i + 1]) - s1;
      v0 += a * a + b * b; v1 += c * c + d * d;
    }
    v0 = qsum(v0); v1 = qsum(v1);
    if (t < 2) ((float2*)(hp + 640))[w * 16 + g + t * 8] = t ? make_float2(s1, v1) : make_float2(s0, v0);
    __syncwarp();
    if (lane == 0) mbar_arrive(bar + 8 * (B_SB + mh * 8));
  }
  asm volatile("setmaxnreg.inc.sync.aligned.u32 200;");
  uint32_t ga[48];
  {
    float acc[64], acd[32];
    const uint32_t ep = lds32(sb + SM_EP);
    const uint32_t* const fl = g_cnt + C_H + rh * 32 + ((j + lane) & 7);
    const uint4* const hp = g_H + rh * 8 * 672 + w * 160 + lane;
    const uint32_t zz = lds32(sb + SM_K4 + 8);
    uint4 raw[NRAW];
#pragma unroll
    for (int k = 0; k < 5; k++) {
      raw[k] = make_uint4(xr[4 * k] ^ zz, xr[4 * k + 1] ^ zz, xr[4 * k + 2] ^ zz, xr[4 * k + 3] ^ zz);
    }
    uint32_t rdy = 0;
    float2 pa, pb, pc, pd;
    float r0, r1, c0, c1;
    auto fetch = [&](int f) {
      if (f % 5 == 0) {
        poll_bit(rdy, 1u << (f / 5), fl, ep);
      }
      raw[f % NRAW] = ldcg128(hp + ((j + f / 5) & 7) * 672 + (f % 5) * 32);
    };
#pragma unroll
    for (int f = 0; f < 35; f++) {
      const int s = f / 5, k = f % 5;
      if (f == 5) {
#pragma unroll
        for (int n = 5; n < NRAW; n++) fetch(n);
      }
      if (f >= 3) wwait<2>();
      if (s && k == 2 && tid_now() % 32 == 0) mbar_arrive2(bar + 8 * (B_DW + s - 1));
      if (f == 5) { fetch(NRAW); fetch(NRAW + 1); }
      if (f >= 5 && f - 3 + NRAW < 40) fetch(f - 3 + NRAW);
      if (f == 43 - NRAW) {
        const float2* sp = (const float2*)(g_H + (rh * 8 + 2 * t) * 672 + 640) + w * 16 + g;
        pa = ldcg_f2(sp); pb = ldcg_f2(sp + 1344); pc = ldcg_f2(sp + 8); pd = ldcg_f2(sp + 1352);
      }
      if (f == 34) {
        const float mean0 = qsum(pa.x + pb.x) * 0.125f, mean1 = qsum(pc.x + pd.x) * 0.125f;
        const float e0 = pa.x - mean0, e1 = pb.x - mean0, e2 = pc.x - mean1, e3 = pd.x - mean1;
        r0 = rsqrtf(qsum(pa.y + pb.y + 80.f * (e0 * e0 + e1 * e1)) * (1.f / 640.f) + 1e-5f);
        r1 = rsqrtf(qsum(pc.y + pd.y + 80.f * (e2 * e2 + e3 * e3)) * (1.f / 640.f) + 1e-5f);
        c0 = -mean0 * r0; c1 = -mean1 * r1;
      }
      if (k == 0) {
        mbar_wait(bar + 8 * (B_FW + s));
      }
      const uint4 a = raw[f % NRAW];
      wfence();
      if (f == 0) {
        wgmma_rs_n128_tb1_z<HSW>(acc, a.x, a.y, a.z, a.w, dlo(6 * 30 * KB, 10 * KB));
        wgmma_rs_n64_tb1_z<HSW>(acd, a.x, a.y, a.z, a.w, dlo(6 * 30 * KB + 20 * KB, 10 * KB));
      } else {
        wgmma_rs_n128_tb1_a<HSW>(acc, a.x, a.y, a.z, a.w, dlo((s + 6) % 7 * 30 * KB + k * 2 * KB, 10 * KB));
        wgmma_rs_n64_tb1_a<HSW>(acd, a.x, a.y, a.z, a.w, dlo((s + 6) % 7 * 30 * KB + k * 2 * KB + 20 * KB, 10 * KB));
      }
      wcommit();
    }
    mbar_wait(bar + 8 * (B_FW + 7));
    wfence();
#pragma unroll
    for (int k = 0; k < 5; k++) { const uint4 a = raw[(35 + k) % NRAW]; wgmma_rs_n64_tb1_a<HSW>(acd, a.x, a.y, a.z, a.w, dlo(6 * 30 * KB + k * 2 * KB + 20 * KB, 10 * KB)); }
    wcommit();
#pragma unroll
    for (int k = 0; k < 5; k++) { const uint4 a = raw[(35 + k) % NRAW]; wgmma_rs_n128_tb1_a<HSW>(acc, a.x, a.y, a.z, a.w, dlo(6 * 30 * KB + k * 2 * KB, 10 * KB)); }
    wcommit();
    wwait<2>();
    if (tid_now() % 32 == 0) mbar_arrive2(bar + 8 * (B_DW + 6));
    const uint32_t tb = sb + SM_B1 + (tid_now() & 3) * 16;
    float tt[64];
#pragma unroll
    for (int i = 0; i < 8; i++) {
      const float4 b = lds128f(tb + i * 64);
      tt[4 * i] = fmaf(c0, b.x, b.z); tt[4 * i + 1] = fmaf(c0, b.y, b.w); tt[4 * i + 2] = fmaf(c1, b.x, b.z); tt[4 * i + 3] = fmaf(c1, b.y, b.w);
    }
    wwait<1>();
    keep(acd);
#pragma unroll
    for (int i = 0; i < 8; i++) {
      const float4 b = lds128f(tb + (16 + i) * 64);
      ga[32 + 2 * i] = relu2_pair(fmaf(acd[4 * i], r0, fmaf(c0, b.x, b.z)), fmaf(acd[4 * i + 1], r0, fmaf(c0, b.y, b.w)));
      ga[33 + 2 * i] = relu2_pair(fmaf(acd[4 * i + 2], r1, fmaf(c1, b.x, b.z)), fmaf(acd[4 * i + 3], r1, fmaf(c1, b.y, b.w)));
    }
#pragma unroll
    for (int i = 8; i < 16; i++) {
      const float4 b = lds128f(tb + i * 64);
      tt[4 * i] = fmaf(c0, b.x, b.z); tt[4 * i + 1] = fmaf(c0, b.y, b.w); tt[4 * i + 2] = fmaf(c1, b.x, b.z); tt[4 * i + 3] = fmaf(c1, b.y, b.w);
    }
    keep(tt);
    wwait<0>();
    keep(acc);
    if (tid_now() % 32 == 0) mbar_arrive2(bar + 8 * (B_DW + 7));
#pragma unroll
    for (int i = 0; i < 16; i++) {
      ga[2 * i] = relu2_pair(fmaf(acc[4 * i], r0, tt[4 * i]), fmaf(acc[4 * i + 1], r0, tt[4 * i + 1]));
      ga[2 * i + 1] = relu2_pair(fmaf(acc[4 * i + 2], r1, tt[4 * i + 2]), fmaf(acc[4 * i + 3], r1, tt[4 * i + 3]));
    }
#pragma unroll
    for (int i = 0; i < 48; i++) asm volatile("" : "+r"(ga[i])::"memory");
  }
  asm volatile("setmaxnreg.dec.sync.aligned.u32 120;");
  const int tid = tid_now() & 127;
  const bool lane0 = (tid & 31) == 0;
  if (lane0) mbar_arrive(bar + 8 * (B_GDONE + mh));
  {
    float x[24], y[16];
    uint4* const pp = g_P + ((rb * 16 + mh) * 8 + j) * 640 + w * 160 + (tid & 31);
    uint32_t b = dlo(0, KB);
    mbar_wait(bar + 8 * (B_FW + 8));
    wfence();
    ffn2_x(x, ga, b);
    wcommit();
#pragma unroll 1
    for (int s = 1; s < 8; s++) {
      uint4* d = pp + ((j + s) & 7) * 10240;
      wfence();
      ffn2_y(y, ga, b);
      wcommit();
      b = s == 7 ? dlo(0, KB) : b + 30 * KB / 16;
      mbar_wait(bar + 8 * (B_FW + 8 + s));
      wwait<1>();
      keep(x);
      store_frag(d, x);
      wfence();
      ffn2_x(x, ga, b);
      wcommit();
      wwait<1>();
      keep(y);
      store_frag(d + 96, y);
      __syncwarp();
      if (lane0) {
        if (s < 7) mbar_arrive(bar + 8 * (B_SB + mh * 8 + s));
        if (s == 1) mbar_arrive2(bar + 8 * (B_DW + 8));
        if (s == 3 - mh) mbar_arrive(bar + 8 * (B_XF + 1 - mh));
      }
    }
    wfence();
    ffn2_y(y, ga, b);
    wcommit();
    fence_pub();
    __syncwarp();
    if (lane0) red_add(g_cnt + C_P + ((rb * 8 + ((j + 7) & 7)) * 2 + mh) * 32 + j, 1);
    mbar_wait(bar + 8 * (B_XF + mh));
    const uint32_t hand = sb + (30 + 30 * mh) * KB + tid * 16;
    wwait<1>();
    keep(x);
#pragma unroll
    for (int i = 0; i < 6; i++) sts128f(hand + i * 2 * KB, make_float4(x[4 * i], x[4 * i + 1], x[4 * i + 2], x[4 * i + 3]));
    wwait<0>();
    keep(y);
#pragma unroll
    for (int i = 0; i < 4; i++) sts128f(hand + (6 + i) * 2 * KB, make_float4(y[4 * i], y[4 * i + 1], y[4 * i + 2], y[4 * i + 3]));
    __syncwarp();
    if (lane0) mbar_arrive(bar + 8 * (B_ADONE + mh));
  }
}

typedef CUresult (*EncodeFn)(CUtensorMap*, CUtensorMapDataType, cuuint32_t, void*, const cuuint64_t*, const cuuint64_t*, const cuuint32_t*,
                             const cuuint32_t*, CUtensorMapInterleave, CUtensorMapSwizzle, CUtensorMapL2promotion, CUtensorMapFloatOOBfill);

void make_map(EncodeFn enc, CUtensorMap* m, void* base, int rows, int cols, int br, int wide) {
  const cuuint32_t es[3] = {1, 1, 1};
  if (wide) {
    const cuuint64_t dim[2] = {(cuuint64_t)cols, (cuuint64_t)rows}, str[1] = {(cuuint64_t)cols * 2};
    const cuuint32_t box[2] = {(cuuint32_t)wide, (cuuint32_t)br};
    enc(m, CU_TENSOR_MAP_DATA_TYPE_BFLOAT16, 2, base, dim, str, box, es, CU_TENSOR_MAP_INTERLEAVE_NONE, wide == 64 ? CU_TENSOR_MAP_SWIZZLE_128B : CU_TENSOR_MAP_SWIZZLE_NONE,
        CU_TENSOR_MAP_L2_PROMOTION_L2_128B, CU_TENSOR_MAP_FLOAT_OOB_FILL_NONE);
  } else {
    const cuuint64_t dim[3] = {16, (cuuint64_t)rows, (cuuint64_t)cols / 16}, str[2] = {(cuuint64_t)cols * 2, 32};
    const cuuint32_t box[3] = {16, (cuuint32_t)br, 5};
    enc(m, CU_TENSOR_MAP_DATA_TYPE_BFLOAT16, 3, base, dim, str, box, es, CU_TENSOR_MAP_INTERLEAVE_NONE, CU_TENSOR_MAP_SWIZZLE_32B,
        CU_TENSOR_MAP_L2_PROMOTION_NONE, CU_TENSOR_MAP_FLOAT_OOB_FILL_NONE);
  }
}

}

extern "C" void kernel_launch(void* const* d_in, const int* in_sizes, int n_in, void* d_out, int out_size) {
  static EncodeFn enc = nullptr;
  if (!enc) {
    void* fn = nullptr;
    cudaDriverEntryPointQueryResult qr;
    cudaGetDriverEntryPoint("cuTensorMapEncodeTiled", &fn, cudaEnableDefault, &qr);
    enc = (EncodeFn)fn;
    cudaFuncSetAttribute(block_kernel, cudaFuncAttributeMaxDynamicSharedMemorySize, SMEM_BYTES);
  }
  Params p;
  p.x = (const __nv_bfloat16*)d_in[0]; p.wqkv = (const __nv_bfloat16*)d_in[1]; p.wo = (const __nv_bfloat16*)d_in[2];
  p.w1 = (const __nv_bfloat16*)d_in[4]; p.b1 = (const __nv_bfloat16*)d_in[5]; p.w2 = (const __nv_bfloat16*)d_in[6];
  p.b2 = (const __nv_bfloat16*)d_in[7]; p.out = (__nv_bfloat16*)d_out;
  Maps tm;
  make_map(enc, &tm.x, d_in[0], 2048, 640, 128, 64);
  make_map(enc, &tm.wqkv, d_in[1], 640, 1920, 64, 64);
  make_map(enc, &tm.wo, d_in[2], 640, 640, 128, 0);
  make_map(enc, &tm.w1, d_in[4], 640, 1536, 80, 64);
  make_map(enc, &tm.w2, d_in[6], 1536, 640, 32, 0);
  make_map(enc, &tm.wcs, d_in[1], 640, 1920, 160, 32);
  block_kernel<<<128, 640, SMEM_BYTES>>>(tm, p);
}
```
